```python
import torch

def _softmax(x, axis=-1):
    return torch.softmax(x, dim=axis)
def _gelu(x):
    return torch.nn.functional.gelu(x, approximate="tanh")
def _silu(x):
    return torch.nn.functional.silu(x)
def _sigmoid(x):
    return torch.sigmoid(x)
def _layernorm(x, axis=-1, eps=1e-5):
    m = x.mean(dim=axis, keepdim=True)
    v = x.var(dim=axis, keepdim=True, unbiased=False)
    return (x - m) / torch.sqrt(v + eps)
def _scatter_add(tgt, idx, src, axis=0):
    return tgt.clone().index_add_(axis, idx, src)
def _segment_sum(src, seg, n):
    out = torch.zeros((n,) + src.shape[1:], dtype=src.dtype)
    return out.index_add_(0, seg, src)
def _pad(x, pw):
    flat = tuple(v for pair in reversed(pw) for v in pair)
    return torch.nn.functional.pad(x, flat)

kernel_name = 'concat_heads__spectral_fnet__sliding_block__prompt'

def setup_inputs():

    _w = (lambda a: (lambda t: t.to(torch.bfloat16) if t.is_floating_point() else t)(torch.as_tensor(a)))
    def _A_setup():
        B, S, D = 1, 2048, 512
        ns = torch.arange(S)[:, None] * torch.arange(S)[None, :]
        nd = torch.arange(D)[:, None] * torch.arange(D)[None, :]
        Ws_re = torch.cos(-2.0 * torch.pi * ns / S).to(float)
        Ws_im = torch.sin(-2.0 * torch.pi * ns / S).to(float)
        Wd_re = torch.cos(-2.0 * torch.pi * nd / D).to(float)
        Wd_im = torch.sin(-2.0 * torch.pi * nd / D).to(float)
        return {
            "x": _w((lambda *s: torch.randn(*s, dtype=torch.bfloat16) * 0.05)(B, S, D)),
            "dft_seq_re": _w(Ws_re),
            "dft_seq_im": _w(Ws_im),
            "dft_hid_re": _w(Wd_re),
            "dft_hid_im": _w(Wd_im),
        }
    _A_in = _A_setup()

    def _B_setup():
        B, S, D = 1, 2048, 512
        return {
            "x": _w((lambda *s: torch.randn(*s, dtype=torch.bfloat16) * 0.2)(B, S, D)),
            "wqkv": _w((lambda *s: torch.randn(*s, dtype=torch.bfloat16) * 0.8)(D, 3 * D)),
            "wo": _w((lambda *s: torch.randn(*s, dtype=torch.bfloat16) * 0.2)(D, D)),
        }
    _B_in = _B_setup()

    return {
        "A_x": _A_in["x"],
        "A_dft_seq_re": _A_in["dft_seq_re"],
        "A_dft_seq_im": _A_in["dft_seq_im"],
        "A_dft_hid_re": _A_in["dft_hid_re"],
        "A_dft_hid_im": _A_in["dft_hid_im"],
        "B_x": _B_in["x"],
        "B_wqkv": _B_in["wqkv"],
        "B_wo": _B_in["wo"],
    }

def reference(A_x, A_dft_seq_re, A_dft_seq_im, A_dft_hid_re, A_dft_hid_im, B_x, B_wqkv, B_wo):
    def _A_ref(x, dft_seq_re, dft_seq_im, dft_hid_re, dft_hid_im):
        a = torch.einsum("bsd,ed->bse", x, dft_hid_re)
        b = torch.einsum("bsd,ed->bse", x, dft_hid_im)
        y = torch.einsum("ts,bse->bte", dft_seq_re, a) - torch.einsum("ts,bse->bte", dft_seq_im, b)
        return y

    def _B_ref(x, wqkv, wo):
        B, S, D = x.shape
        H = 32; Dh = D // H; W = 256
        qkv = (lambda x, *d: x.permute(*d))((x @ wqkv).reshape(B, S, 3, H, Dh), 2, 0, 3, 1, 4)
        q, k, v = qkv[0], qkv[1], qkv[2]
        scores = torch.einsum("bhqd,bhkd->bhqk", q, k) * (Dh ** -0.5)
        idx = torch.arange(S)
        mask = (idx[:, None] - idx[None, :] >= 0) & (idx[:, None] - idx[None, :] < W)
        scores = torch.where(mask[None, None], scores, -1e9)
        p = _softmax(scores, axis=-1)
        o = torch.einsum("bhqk,bhkd->bhqd", p, v)
        return (lambda x, *d: x.permute(*d))(o, 0, 2, 1, 3).reshape(B, S, D) @ wo

    a = _A_ref(A_x, A_dft_seq_re, A_dft_seq_im, A_dft_hid_re, A_dft_hid_im)
    b = _B_ref(B_x, B_wqkv, B_wo)
    return torch.concatenate([a, b], axis=-1)
```

```cpp
#include <cuda_runtime.h>
#include <cuda_bf16.h>
#include <cuda.h>
#include <stdint.h>

namespace {

constexpr int NX = 36;
constexpr int NY = 64 - NX;
constexpr float SC = 0.25f * 1.4426950408889634f;

constexpr uint32_t OFF_RING = 0;
constexpr uint32_t OFF_KV = 163840;
constexpr uint32_t OFF_QS = 212992;
constexpr uint32_t OFF_ONES = 229376;
constexpr uint32_t OFF_BAR = 229888;
constexpr uint32_t SMEM_BYTES = OFF_BAR + 256 + 1024;
constexpr uint32_t B_FULLA = 0, B_EMPTYA = 40, B_FULLB = 80, B_EMPTYB = 112, B_KVFULL = 144, B_KVEMPTY = 160,
                   B_STG = 176, B_KVSTG = 184, B_ATT = 192;

constexpr int F_A = 0, F_KV = 4, F_O = 132, F_P = 148, F_DONE = 212, F_COUNT = 213;

struct __align__(64) Params {
  CUtensorMap xa, wr, wi, xb, wqkv, cr, ci, ab, o, wo, out;
  const uint8_t* p_xa; const uint8_t* p_wr; const uint8_t* p_wi; const uint8_t* p_xb; const uint8_t* p_wqkv;
  const uint8_t* p_wo; const uint8_t* p_cr; const uint8_t* p_ci;
};

__device__ __align__(1024) __nv_bfloat16 g_ab[4096 * 512];
__device__ __align__(1024) __nv_bfloat16 g_o[2048 * 512];
__device__ __align__(1024) uint8_t g_kv[32 * 32 * 4096];
__device__ __align__(1024) float4 g_part[64 * 32 * 128];
__device__ __align__(1024) unsigned g_flags[F_COUNT * 32];

__device__ __forceinline__ uint32_t smem_u32(const void* p) { return (uint32_t)__cvta_generic_to_shared(p); }
__device__ __forceinline__ void mbar_init(uint32_t bar, uint32_t count) {
  asm volatile("mbarrier.init.shared::cta.b64 [%0], %1;" ::"r"(bar), "r"(count) : "memory");
}
__device__ __forceinline__ void mbar_expect_tx(uint32_t bar, uint32_t bytes) {
  asm volatile("mbarrier.arrive.expect_tx.shared::cta.b64 _, [%0], %1;" ::"r"(bar), "r"(bytes) : "memory");
}
__device__ __forceinline__ void mbar_arrive(uint32_t bar) {
  asm volatile("mbarrier.arrive.shared::cta.b64 _, [%0];" ::"r"(bar) : "memory");
}
__device__ __forceinline__ void mbar_arrive_cluster(uint32_t bar, uint32_t cta) {
  asm volatile("{\n.reg .b32 ra;\nmapa.shared::cluster.u32 ra, %0, %1;\nmbarrier.arrive.shared::cluster.b64 _, [ra];\n}" ::"r"(bar), "r"(cta) : "memory");
}
__device__ __forceinline__ void mbar_wait(uint32_t bar, uint32_t parity) {
  asm volatile("{\n.reg .pred p;\n.reg .u32 c;\nmov.u32 c, 0;\n"
               "LAB_WAIT:\nmbarrier.try_wait.parity.shared::cta.b64 p, [%0], %1;\n@p bra LAB_DONE;\n"
               "add.u32 c, c, 1;\nsetp.lt.u32 p, c, 1048576;\n@p bra LAB_WAIT;\ntrap;\nLAB_DONE:\n}"
               ::"r"(bar), "r"(parity) : "memory");
}
__device__ __forceinline__ void flag_wait(const unsigned* f, unsigned target) {
  asm volatile("{\n.reg .pred p;\n.reg .u32 c, v;\nmov.u32 c, 0;\n"
               "LAB_WAIT:\nld.acquire.gpu.global.u32 v, [%0];\nsetp.ge.u32 p, v, %1;\n@p bra LAB_DONE;\n"
               "add.u32 c, c, 1;\nsetp.lt.u32 p, c, 1048576;\n@p bra LAB_WAIT;\ntrap;\nLAB_DONE:\nfence.proxy.async;\n}"
               ::"l"(f), "r"(target) : "memory");
}
__device__ __forceinline__ void flag_add(unsigned* f) {
  asm volatile("red.release.gpu.global.add.u32 [%0], 1;" ::"l"(f) : "memory");
}
__device__ __forceinline__ void tma_load(uint32_t dst, const CUtensorMap* map, int c0, int c1, uint32_t bar) {
  asm volatile("cp.async.bulk.tensor.2d.shared::cluster.global.mbarrier::complete_tx::bytes [%0], [%1, {%3, %4}], [%2];"
               ::"r"(dst), "l"(map), "r"(bar), "r"(c0), "r"(c1) : "memory");
}
__device__ __forceinline__ void tma_load_mc(uint32_t dst, const CUtensorMap* map, int c0, int c1, uint32_t bar) {
  asm volatile("cp.async.bulk.tensor.2d.shared::cluster.global.mbarrier::complete_tx::bytes.multicast::cluster [%0], [%1, {%3, %4}], [%2], %5;"
               ::"r"(dst), "l"(map), "r"(bar), "r"(c0), "r"(c1), "h"((uint16_t)3) : "memory");
}
__device__ __forceinline__ void tma_store(const CUtensorMap* map, uint32_t src, int c0, int c1) {
  asm volatile("cp.async.bulk.tensor.2d.global.shared::cta.bulk_group [%0, {%2, %3}], [%1];"
               ::"l"(map), "r"(src), "r"(c0), "r"(c1) : "memory");
}
__device__ __forceinline__ void bulk_load(uint32_t dst, const void* src, uint32_t bytes, uint32_t bar) {
  asm volatile("cp.async.bulk.shared::cluster.global.mbarrier::complete_tx::bytes [%0], [%1], %2, [%3];"
               ::"r"(dst), "l"(src), "r"(bytes), "r"(bar) : "memory");
}
__device__ __forceinline__ void bulk_store(void* dst, uint32_t src, uint32_t bytes) {
  asm volatile("cp.async.bulk.global.shared::cta.bulk_group [%0], [%1], %2;" ::"l"(dst), "r"(src), "r"(bytes) : "memory");
}
__device__ __forceinline__ void bulk_commit() { asm volatile("cp.async.bulk.commit_group;" ::: "memory"); }
__device__ __forceinline__ void bulk_wait_all() { asm volatile("cp.async.bulk.wait_group 0;" ::: "memory"); }
__device__ __forceinline__ void bulk_wait_read() { asm volatile("cp.async.bulk.wait_group.read 0;" ::: "memory"); }
__device__ __forceinline__ void l2_prefetch(const void* p, uint32_t bytes) {
  asm volatile("cp.async.bulk.prefetch.L2.global [%0], %1;" ::"l"(p), "r"(bytes) : "memory");
}
__device__ __forceinline__ void map_prefetch(const CUtensorMap* m) {
  asm volatile("prefetch.tensormap [%0];" ::"l"(m) : "memory");
}
__device__ __forceinline__ void cluster_sync() {
  asm volatile("barrier.cluster.arrive.release.aligned;\nbarrier.cluster.wait.acquire.aligned;" ::: "memory");
}
template <int ID> __device__ __forceinline__ void named_bar() { asm volatile("bar.sync %0, 128;" ::"n"(ID) : "memory"); }
__device__ __forceinline__ void named_bar23(int a) { if (a == 0) named_bar<2>(); else named_bar<3>(); }
__device__ __forceinline__ void wgmma_fence() { asm volatile("wgmma.fence.sync.aligned;" ::: "memory"); }
__device__ __forceinline__ void wgmma_commit() { asm volatile("wgmma.commit_group.sync.aligned;" ::: "memory"); }
template <int N> __device__ __forceinline__ void wgmma_wait() { asm volatile("wgmma.wait_group.sync.aligned %0;" ::"n"(N) : "memory"); }
template <int R> __device__ __forceinline__ void reg_alloc() { asm volatile("setmaxnreg.inc.sync.aligned.u32 %0;" ::"n"(R)); }
template <int R> __device__ __forceinline__ void reg_dealloc() { asm volatile("setmaxnreg.dec.sync.aligned.u32 %0;" ::"n"(R)); }
__device__ __forceinline__ void fence_async_smem() { asm volatile("fence.proxy.async.shared::cta;" ::: "memory"); }
__device__ __forceinline__ void fence_async_all() { asm volatile("fence.proxy.async;" ::: "memory"); }
__device__ __forceinline__ float ex2(float x) { float y; asm("ex2.approx.ftz.f32 %0, %1;" : "=f"(y) : "f"(x)); return y; }
__device__ __forceinline__ float rcpf(float x) { float y; asm("rcp.approx.ftz.f32 %0, %1;" : "=f"(y) : "f"(x)); return y; }
__device__ __forceinline__ uint32_t pack2(float lo, float hi) {
  uint32_t r; asm("cvt.rn.bf16x2.f32 %0, %1, %2;" : "=r"(r) : "f"(hi), "f"(lo)); return r;
}
__device__ __forceinline__ void stsm4(uint32_t addr, uint32_t r0, uint32_t r1, uint32_t r2, uint32_t r3) {
  asm volatile("stmatrix.sync.aligned.m8n8.x4.shared.b16 [%0], {%1, %2, %3, %4};" ::"r"(addr), "r"(r0), "r"(r1), "r"(r2), "r"(r3) : "memory");
}
template <int N> __device__ __forceinline__ void fregs(float (&a)[N]) {
#pragma unroll
  for (int i = 0; i < N; i++) asm volatile("" : "+f"(a[i])::"memory");
}
template <int N> __device__ __forceinline__ void fregs(uint32_t (&a)[N]) {
#pragma unroll
  for (int i = 0; i < N; i++) asm volatile("" : "+r"(a[i])::"memory");
}
__device__ __forceinline__ uint64_t desc128(uint32_t lo) { return ((uint64_t)0x40000040u << 32) | lo; }
__device__ __forceinline__ uint64_t desc32(uint32_t lo) { return ((uint64_t)0xC0000010u << 32) | lo; }

template<int TB>
__device__ __forceinline__ void wgmma_ss_n128(float (&d)[64], uint64_t da, uint64_t db) {
  asm volatile("{\n.reg .pred p;\nsetp.ne.b32 p, 1, 0;\nwgmma.mma_async.sync.aligned.m64n128k16.f32.bf16.bf16 "
    "{%0, %1, %2, %3, %4, %5, %6, %7, %8, %9, %10, %11, %12, %13, %14, %15, %16, %17, %18, %19, %20, %21, %22, %23, %24, %25, %26, %27, %28, %29, %30, %31, "
    "%32, %33, %34, %35, %36, %37, %38, %39, %40, %41, %42, %43, %44, %45, %46, %47, %48, %49, %50, %51, %52, %53, %54, %55, %56, %57, %58, %59, %60, %61, "
    "%62, %63}"
    ", %64, %65, p, 1, 1, 0, %66;\n}\n"
    :
      "+f"(d[0]), "+f"(d[1]), "+f"(d[2]), "+f"(d[3]), "+f"(d[4]), "+f"(d[5]), "+f"(d[6]), "+f"(d[7]), "+f"(d[8]), "+f"(d[9]), "+f"(d[10]), "+f"(d[11]),
      "+f"(d[12]), "+f"(d[13]), "+f"(d[14]), "+f"(d[15]), "+f"(d[16]), "+f"(d[17]), "+f"(d[18]), "+f"(d[19]), "+f"(d[20]), "+f"(d[21]), "+f"(d[22]),
      "+f"(d[23]), "+f"(d[24]), "+f"(d[25]), "+f"(d[26]), "+f"(d[27]), "+f"(d[28]), "+f"(d[29]), "+f"(d[30]), "+f"(d[31]), "+f"(d[32]), "+f"(d[33]),
      "+f"(d[34]), "+f"(d[35]), "+f"(d[36]), "+f"(d[37]), "+f"(d[38]), "+f"(d[39]), "+f"(d[40]), "+f"(d[41]), "+f"(d[42]), "+f"(d[43]), "+f"(d[44]),
      "+f"(d[45]), "+f"(d[46]), "+f"(d[47]), "+f"(d[48]), "+f"(d[49]), "+f"(d[50]), "+f"(d[51]), "+f"(d[52]), "+f"(d[53]), "+f"(d[54]), "+f"(d[55]),
      "+f"(d[56]), "+f"(d[57]), "+f"(d[58]), "+f"(d[59]), "+f"(d[60]), "+f"(d[61]), "+f"(d[62]), "+f"(d[63])
    : "l"(da), "l"(db), "n"(TB));
}

template<int TB>
__device__ __forceinline__ void wgmma_ss_n192(float (&d)[96], uint64_t da, uint64_t db) {
  asm volatile("{\n.reg .pred p;\nsetp.ne.b32 p, 1, 0;\nwgmma.mma_async.sync.aligned.m64n192k16.f32.bf16.bf16 "
    "{%0, %1, %2, %3, %4, %5, %6, %7, %8, %9, %10, %11, %12, %13, %14, %15, %16, %17, %18, %19, %20, %21, %22, %23, %24, %25, %26, %27, %28, %29, %30, %31, "
    "%32, %33, %34, %35, %36, %37, %38, %39, %40, %41, %42, %43, %44, %45, %46, %47, %48, %49, %50, %51, %52, %53, %54, %55, %56, %57, %58, %59, %60, %61, "
    "%62, %63, %64, %65, %66, %67, %68, %69, %70, %71, %72, %73, %74, %75, %76, %77, %78, %79, %80, %81, %82, %83, %84, %85, %86, %87, %88, %89, %90, %91, "
    "%92, %93, %94, %95}"
    ", %96, %97, p, 1, 1, 0, %98;\n}\n"
    :
      "+f"(d[0]), "+f"(d[1]), "+f"(d[2]), "+f"(d[3]), "+f"(d[4]), "+f"(d[5]), "+f"(d[6]), "+f"(d[7]), "+f"(d[8]), "+f"(d[9]), "+f"(d[10]), "+f"(d[11]),
      "+f"(d[12]), "+f"(d[13]), "+f"(d[14]), "+f"(d[15]), "+f"(d[16]), "+f"(d[17]), "+f"(d[18]), "+f"(d[19]), "+f"(d[20]), "+f"(d[21]), "+f"(d[22]),
      "+f"(d[23]), "+f"(d[24]), "+f"(d[25]), "+f"(d[26]), "+f"(d[27]), "+f"(d[28]), "+f"(d[29]), "+f"(d[30]), "+f"(d[31]), "+f"(d[32]), "+f"(d[33]),
      "+f"(d[34]), "+f"(d[35]), "+f"(d[36]), "+f"(d[37]), "+f"(d[38]), "+f"(d[39]), "+f"(d[40]), "+f"(d[41]), "+f"(d[42]), "+f"(d[43]), "+f"(d[44]),
      "+f"(d[45]), "+f"(d[46]), "+f"(d[47]), "+f"(d[48]), "+f"(d[49]), "+f"(d[50]), "+f"(d[51]), "+f"(d[52]), "+f"(d[53]), "+f"(d[54]), "+f"(d[55]),
      "+f"(d[56]), "+f"(d[57]), "+f"(d[58]), "+f"(d[59]), "+f"(d[60]), "+f"(d[61]), "+f"(d[62]), "+f"(d[63]), "+f"(d[64]), "+f"(d[65]), "+f"(d[66]),
      "+f"(d[67]), "+f"(d[68]), "+f"(d[69]), "+f"(d[70]), "+f"(d[71]), "+f"(d[72]), "+f"(d[73]), "+f"(d[74]), "+f"(d[75]), "+f"(d[76]), "+f"(d[77]),
      "+f"(d[78]), "+f"(d[79]), "+f"(d[80]), "+f"(d[81]), "+f"(d[82]), "+f"(d[83]), "+f"(d[84]), "+f"(d[85]), "+f"(d[86]), "+f"(d[87]), "+f"(d[88]),
      "+f"(d[89]), "+f"(d[90]), "+f"(d[91]), "+f"(d[92]), "+f"(d[93]), "+f"(d[94]), "+f"(d[95])
    : "l"(da), "l"(db), "n"(TB));
}

template<int TB, int ACC>
__device__ __forceinline__ void wgmma_rs_n64(float (&d)[32], uint32_t a0, uint32_t a1, uint32_t a2, uint32_t a3, uint64_t db) {
  asm volatile("{\n.reg .pred p;\nsetp.ne.b32 p, %38, 0;\nwgmma.mma_async.sync.aligned.m64n64k16.f32.bf16.bf16 "
    "{%0, %1, %2, %3, %4, %5, %6, %7, %8, %9, %10, %11, %12, %13, %14, %15, %16, %17, %18, %19, %20, %21, %22, %23, %24, %25, %26, %27, %28, %29, %30, %31}"
    ", {%32, %33, %34, %35}, %36, p, 1, 1, %37;\n}\n"
    :
      "+f"(d[0]), "+f"(d[1]), "+f"(d[2]), "+f"(d[3]), "+f"(d[4]), "+f"(d[5]), "+f"(d[6]), "+f"(d[7]), "+f"(d[8]), "+f"(d[9]), "+f"(d[10]), "+f"(d[11]),
      "+f"(d[12]), "+f"(d[13]), "+f"(d[14]), "+f"(d[15]), "+f"(d[16]), "+f"(d[17]), "+f"(d[18]), "+f"(d[19]), "+f"(d[20]), "+f"(d[21]), "+f"(d[22]),
      "+f"(d[23]), "+f"(d[24]), "+f"(d[25]), "+f"(d[26]), "+f"(d[27]), "+f"(d[28]), "+f"(d[29]), "+f"(d[30]), "+f"(d[31])
    : "r"(a0), "r"(a1), "r"(a2), "r"(a3), "l"(db), "n"(TB), "n"(ACC));
}

template<int TB, int ACC>
__device__ __forceinline__ void wgmma_rs_n24(float (&d)[12], uint32_t a0, uint32_t a1, uint32_t a2, uint32_t a3, uint64_t db) {
  asm volatile("{\n.reg .pred p;\nsetp.ne.b32 p, %18, 0;\nwgmma.mma_async.sync.aligned.m64n24k16.f32.bf16.bf16 "
    "{%0, %1, %2, %3, %4, %5, %6, %7, %8, %9, %10, %11}"
    ", {%12, %13, %14, %15}, %16, p, 1, 1, %17;\n}\n"
    :
      "+f"(d[0]), "+f"(d[1]), "+f"(d[2]), "+f"(d[3]), "+f"(d[4]), "+f"(d[5]), "+f"(d[6]), "+f"(d[7]), "+f"(d[8]), "+f"(d[9]), "+f"(d[10]), "+f"(d[11])
    : "r"(a0), "r"(a1), "r"(a2), "r"(a3), "l"(db), "n"(TB), "n"(ACC));
}


__device__ __forceinline__ void stage_tile(const float (&d)[64], uint32_t stg, int w, int lane, float sgn) {
  const int r = 16 * w + (lane & 7) + ((lane >> 3) & 1) * 8;
  const uint32_t rowa = stg + r * 128;
  const int hi = lane >> 4, sw = r & 7;
#pragma unroll
  for (int jj = 0; jj < 8; jj++) {
    const int chunk = 2 * (jj & 3) + hi;
    const uint32_t addr = rowa + (jj >> 2) * 8192 + ((chunk ^ sw) << 4);
    stsm4(addr, pack2(d[8 * jj] * sgn, d[8 * jj + 1] * sgn), pack2(d[8 * jj + 2] * sgn, d[8 * jj + 3] * sgn),
          pack2(d[8 * jj + 4] * sgn, d[8 * jj + 5] * sgn), pack2(d[8 * jj + 6] * sgn, d[8 * jj + 7] * sgn));
  }
}

__device__ __forceinline__ void rowmax(const float (&s)[32], float& x0, float& x1) {
  float a0 = fmaxf(s[0], s[1]), a1 = fmaxf(s[2], s[3]), b0 = fmaxf(s[4], s[5]), b1 = fmaxf(s[6], s[7]);
#pragma unroll
  for (int i = 8; i < 32; i += 8) {
    a0 = fmaxf(a0, fmaxf(s[i], s[i + 1])); a1 = fmaxf(a1, fmaxf(s[i + 2], s[i + 3]));
    b0 = fmaxf(b0, fmaxf(s[i + 4], s[i + 5])); b1 = fmaxf(b1, fmaxf(s[i + 6], s[i + 7]));
  }
  x0 = fmaxf(a0, b0); x1 = fmaxf(a1, b1);
  x0 = fmaxf(x0, __shfl_xor_sync(~0u, x0, 1)); x1 = fmaxf(x1, __shfl_xor_sync(~0u, x1, 1));
  x0 = fmaxf(x0, __shfl_xor_sync(~0u, x0, 2)); x1 = fmaxf(x1, __shfl_xor_sync(~0u, x1, 2));
}
__device__ __forceinline__ void exps(const float (&s)[32], float mc0, float mc1, uint32_t (&p)[16]) {
#pragma unroll
  for (int i = 0; i < 16; i++) {
    const float mc = (i & 1) ? mc1 : mc0;
    p[i] = pack2(ex2(fmaf(s[2 * i], SC, mc)), ex2(fmaf(s[2 * i + 1], SC, mc)));
  }
}
template <int FIRST>
__device__ __forceinline__ void issue_pv(float (&o)[12], const uint32_t (&p)[16], uint32_t vlo) {
#pragma unroll
  for (int c = 0; c < 4; c++) {
    const uint64_t d = desc32(vlo - (uint32_t)c * (32u * 65535u));
    if (FIRST && c == 0) wgmma_rs_n24<1, 0>(o, p[0], p[1], p[2], p[3], d);
    else wgmma_rs_n24<1, 1>(o, p[c * 4 + 0], p[c * 4 + 1], p[c * 4 + 2], p[c * 4 + 3], d);
  }
}

}

__global__ void __cluster_dims__(2, 1, 1) __launch_bounds__(512, 1)
concat_heads__spectral_fnet__sliding_block__prompt_kernel(const __grid_constant__ Params P, __nv_bfloat16* __restrict__ out) {
  extern __shared__ uint8_t smem_raw[];
  const uint32_t sb = (smem_u32(smem_raw) + 1023) & ~1023u;
  const uint32_t bar = sb + OFF_BAR;
  const uint32_t sd = (sb & 0x3FFFFu) >> 4;
  const int wg = __shfl_sync(~0u, threadIdx.x >> 7, 0);
  const int warp = __shfl_sync(~0u, (threadIdx.x >> 5) & 3, 0);
  const int lane = threadIdx.x & 31;
  const int tid = threadIdx.x & 127;
  const int rank = blockIdx.x & 1;
  const int cl = blockIdx.x >> 1;
  const int rb = cl >> 2;
  const int q4 = cl & 3;
  const int isY = q4 & 1;
  const int cp = q4 >> 1;
  const int eb2 = 2 * cp + rank;
  const int nb1 = 2 * q4 + rank;
  const int tile = rb * 4 + eb2;

  if (threadIdx.x == 0) {
    for (int i = 0; i < 5; i++) { mbar_init(bar + B_FULLA + 8 * i, 1); mbar_init(bar + B_EMPTYA + 8 * i, 4); }
    for (int i = 0; i < 4; i++) { mbar_init(bar + B_FULLB + 8 * i, 1); mbar_init(bar + B_EMPTYB + 8 * i, 4); }
    for (int i = 0; i < 2; i++) { mbar_init(bar + B_KVFULL + 8 * i, 1); mbar_init(bar + B_KVEMPTY + 8 * i, 2); }
    mbar_init(bar + B_STG, 1); mbar_init(bar + B_KVSTG, 2); mbar_init(bar + B_ATT, 2);
    asm volatile("fence.mbarrier_init.release.cluster;" ::: "memory");
    map_prefetch(&P.xa); map_prefetch(&P.wr); map_prefetch(&P.wi);
  } else if (threadIdx.x == 32) {
    map_prefetch(&P.xb); map_prefetch(&P.wqkv); map_prefetch(&P.ab); map_prefetch(&P.cr); map_prefetch(&P.ci);
    map_prefetch(&P.o); map_prefetch(&P.wo); map_prefetch(&P.out);
  } else if (threadIdx.x == 64) {
    l2_prefetch(P.p_xa + blockIdx.x * 16384, 16384);
    l2_prefetch(P.p_wr + blockIdx.x * 4096, 4096);
    l2_prefetch(P.p_wi + blockIdx.x * 4096, 4096);
    l2_prefetch(P.p_xb + blockIdx.x * 16384, 16384);
    l2_prefetch(P.p_wqkv + blockIdx.x * 12288, 12288);
    l2_prefetch(P.p_wo + blockIdx.x * 4096, 4096);
  } else if (threadIdx.x >= 128 && threadIdx.x < 256) {
    asm volatile("st.shared.u32 [%0], %1;" ::"r"(sb + OFF_ONES + tid * 4), "r"(0x3f803f80u) : "memory");
    fence_async_smem();
  }
  __syncthreads();
  cluster_sync();

  if (wg == 0) {
    reg_dealloc<24>();
    if (warp == 0 && lane == 0) {
      uint32_t useA = 0, useB = 0;
      uint32_t p = 2;
      const CUtensorMap* mw = (nb1 & 4) ? &P.wi : &P.wr;
      for (int n = 0; n < 8; n++) {
        mbar_wait(bar + B_EMPTYA + 8 * p, ((useA >> p) & 1) ^ 1);
        const uint32_t st = sb + OFF_RING + p * 32768, fb = bar + B_FULLA + 8 * p;
        mbar_expect_tx(fb, 32768);
        tma_load_mc(st + rank * 8192, &P.xa, n * 64, rb * 128 + rank * 64, fb);
        tma_load(st + 16384, mw, n * 64, (nb1 & 3) * 128, fb);
        useA ^= 1u << p;
        p = (p == 4) ? 0 : p + 1;
      }
      for (int e = 0; e < 8; e++) {
        const uint32_t j = e & 3;
        if (e < 4) mbar_wait(bar + B_EMPTYA + 8 * (e + 1), ((useA >> (e + 1)) & 1) ^ 1);
        else mbar_wait(bar + B_EMPTYB + 8 * j, ((useB >> j) & 1) ^ 1);
        const uint32_t st = sb + OFF_RING + j * 40960, fb = bar + B_FULLB + 8 * j;
        mbar_expect_tx(fb, 40960);
        tma_load_mc(st + rank * 8192, &P.xb, e * 64, rb * 128 + rank * 64, fb);
        tma_load(st + 16384, &P.wqkv, nb1 * 64, e * 64, fb);
        tma_load(st + 24576, &P.wqkv, 512 + nb1 * 64, e * 64, fb);
        tma_load(st + 32768, &P.wqkv, 1024 + nb1 * 64, e * 64, fb);
        useB ^= 1u << j;
      }
      p = 0;
      {
        const int kb0 = isY ? NX : 0, nk = isY ? NY : NX;
        for (int m = 0; m < nk; m++) {
          mbar_wait(bar + B_EMPTYA + 8 * p, ((useA >> p) & 1) ^ 1);
          if (m < 5) {
            const uint32_t j = m < 3 ? m : 3;
            mbar_wait(bar + B_EMPTYB + 8 * j, ((useB >> j) & 1) ^ 1);
            if (m == 0) flag_wait(g_flags + (F_A + eb2) * 32, 32);
          }
          const int kb = kb0 + m;
          const uint32_t st = sb + OFF_RING + p * 32768, fb = bar + B_FULLA + 8 * p;
          mbar_expect_tx(fb, 32768);
          tma_load_mc(st + rank * 8192, kb < 32 ? &P.cr : &P.ci, (kb & 31) * 64, rb * 128 + rank * 64, fb);
          tma_load(st + 16384, &P.ab, eb2 * 128, kb * 64, fb);
          tma_load(st + 24576, &P.ab, eb2 * 128 + 64, kb * 64, fb);
          useA ^= 1u << p;
          p = (p == 4) ? 0 : p + 1;
        }
      }
      if (isY) {
        for (int i = 0; i < 8; i++) {
          mbar_wait(bar + B_EMPTYA + 8 * p, ((useA >> p) & 1) ^ 1);
          if (i == 0) flag_wait(g_flags + (F_O + rb) * 32, 16);
          const uint32_t st = sb + OFF_RING + p * 32768, fb = bar + B_FULLA + 8 * p;
          mbar_expect_tx(fb, 32768);
          tma_load_mc(st + rank * 8192, &P.o, i * 64, rb * 128 + rank * 64, fb);
          tma_load(st + 16384, &P.wo, eb2 * 128, i * 64, fb);
          tma_load(st + 24576, &P.wo, eb2 * 128 + 64, i * 64, fb);
          useA ^= 1u << p;
          p = (p == 4) ? 0 : p + 1;
        }
      } else {
        for (int i = 0; i < 2; i++) {
          mbar_wait(bar + B_EMPTYA + 8 * p, ((useA >> p) & 1) ^ 1);
          if (i == 0) flag_wait(g_flags + (F_P + tile) * 32, 1);
          const uint32_t fb = bar + B_FULLA + 8 * p;
          mbar_expect_tx(fb, 32768);
          bulk_load(sb + OFF_RING + p * 32768, g_part + (size_t)tile * 4096 + i * 2048, 32768, fb);
          useA ^= 1u << p;
          p = (p == 4) ? 0 : p + 1;
        }
      }
    } else if (warp == 1 && lane == 0) {
      const int lb0 = rb >= 2 ? 0 : 4 - 2 * rb;
      mbar_wait(bar + B_KVSTG, 0);
      for (int r = (rb >= 2 ? rb - 2 : 0); r <= rb; r++) flag_wait(g_flags + (F_KV + r * 8 + nb1) * 32, 2);
      for (int h = 0; h < 4; h++) {
        const int b = h & 1;
        if (h >= 2) mbar_wait(bar + B_KVEMPTY + 8 * b, 0);
        const uint32_t bytes = (6 - lb0) * 4096;
        mbar_expect_tx(bar + B_KVFULL + 8 * b, bytes);
        bulk_load(sb + OFF_KV + b * 24576 + lb0 * 4096, g_kv + (size_t)((nb1 * 4 + h) * 32 + 2 * rb - 4 + lb0) * 4096, bytes,
                  bar + B_KVFULL + 8 * b);
      }
    } else if (warp == 2) {
      const int row = rb * 128 + (cp * 2 + rank) * 32 + lane;
      const int k0 = isY ? (NX / 4) : 0, k1 = isY ? 16 : (NX + 3) / 4;
      const long long t0 = clock64();
      for (int q = k0; q < k1; q++) {
        const long long tq = t0 + 1500 + (q - k0) * 1000;
        while (clock64() < tq) __nanosleep(100);
        const uint8_t* src = (q < 8 ? P.p_cr : P.p_ci) + (size_t)row * 4096 + (q & 7) * 512;
        l2_prefetch(src, 512);
      }
    }
    __syncwarp();
    cluster_sync();
    if (threadIdx.x == 0) {
      __threadfence();
      const unsigned old = atomicAdd(g_flags + F_DONE * 32, 1);
      if (old == gridDim.x - 1) {
        for (int i = 0; i < F_COUNT; i++) g_flags[i * 32] = 0;
        __threadfence();
      }
    }
  } else if (wg == 1) {
    reg_alloc<168>();
    float acc0[64], acc1[64];
    uint32_t ph = 0, p = 2;
    const uint32_t rel_pred = (lane == 0);
    const uint32_t rel_cta = warp & 1;
#pragma unroll
    for (int i = 0; i < 64; i++) { acc0[i] = 0.f; acc1[i] = 0.f; }
    fregs(acc0); fregs(acc1);
    uint32_t pprev = 0;
    for (int n = 0; n < 8; n++) {
      mbar_wait(bar + B_FULLA + 8 * p, (ph >> p) & 1);
      ph ^= 1u << p;
      const uint32_t lo = (sd + (OFF_RING >> 4) + p * 2048) | 0x10000u;
      wgmma_fence();
#pragma unroll
      for (int kk = 0; kk < 4; kk++) {
        const uint64_t db = desc128(lo + 1024 + kk * 2);
        wgmma_ss_n128<0>(acc0, desc128(lo + kk * 2), db);
        wgmma_ss_n128<0>(acc1, desc128(lo + 512 + kk * 2), db);
      }
      wgmma_commit();
      if (n > 0) {
        wgmma_wait<1>();
        if (rel_pred) mbar_arrive_cluster(bar + B_EMPTYA + 8 * pprev, rel_cta);
      }
      pprev = p;
      p = (p == 4) ? 0 : p + 1;
    }
    wgmma_wait<0>();
    fregs(acc0); fregs(acc1);
    if (rel_pred) mbar_arrive_cluster(bar + B_EMPTYA + 8 * pprev, rel_cta);
    {
      const float sgn = (nb1 & 4) ? -1.f : 1.f;
      const uint32_t stg = sb + OFF_KV;
      stage_tile(acc0, stg, warp, lane, sgn);
      stage_tile(acc1, stg + 16384, warp, lane, sgn);
      fence_async_smem();
      named_bar<1>();
      if (tid == 0) {
        const int row = (nb1 >> 2) * 2048 + rb * 128, col = (nb1 & 3) * 128;
        tma_store(&P.ab, stg, col, row);
        tma_store(&P.ab, stg + 8192, col + 64, row);
        tma_store(&P.ab, stg + 16384, col, row + 64);
        tma_store(&P.ab, stg + 24576, col + 64, row + 64);
        bulk_commit();
        bulk_wait_all();
        mbar_arrive(bar + B_STG);
        fence_async_all();
        flag_add(g_flags + (F_A + (nb1 & 3)) * 32);
      }
      __syncwarp();
    }
#pragma unroll
    for (int i = 0; i < 64; i++) { acc0[i] = 0.f; acc1[i] = 0.f; }
    fregs(acc0); fregs(acc1);
    p = 0;
    const int nk = isY ? NY : NX;
    for (int m = 0; m < nk; m++) {
      mbar_wait(bar + B_FULLA + 8 * p, (ph >> p) & 1);
      ph ^= 1u << p;
      const uint32_t sta = sd + (OFF_RING >> 4) + p * 2048;
      const uint32_t lo = sta | 0x10000u, lob = (sta + 1024) | (512u << 16);
      wgmma_fence();
#pragma unroll
      for (int kk = 0; kk < 4; kk++) {
        const uint64_t db = desc128(lob + kk * 128);
        wgmma_ss_n128<1>(acc0, desc128(lo + kk * 2), db);
        wgmma_ss_n128<1>(acc1, desc128(lo + 512 + kk * 2), db);
      }
      wgmma_commit();
      if (m > 0) {
        wgmma_wait<1>();
        if (rel_pred) mbar_arrive_cluster(bar + B_EMPTYA + 8 * pprev, rel_cta);
      }
      pprev = p;
      p = (p == 4) ? 0 : p + 1;
    }
    wgmma_wait<0>();
    fregs(acc0); fregs(acc1);
    if (rel_pred) mbar_arrive_cluster(bar + B_EMPTYA + 8 * pprev, rel_cta);
    if (isY) {
      float4* dst = g_part + (size_t)tile * 4096 + tid;
#pragma unroll
      for (int i = 0; i < 16; i++) dst[i * 128] = make_float4(acc0[4 * i], acc0[4 * i + 1], acc0[4 * i + 2], acc0[4 * i + 3]);
#pragma unroll
      for (int i = 0; i < 16; i++) dst[2048 + i * 128] = make_float4(acc1[4 * i], acc1[4 * i + 1], acc1[4 * i + 2], acc1[4 * i + 3]);
      fence_async_all();
      named_bar<1>();
      if (tid == 0) flag_add(g_flags + (F_P + tile) * 32);
    } else {
      const uint32_t stg = sb + OFF_KV;
      mbar_wait(bar + B_ATT, 0);
      mbar_wait(bar + B_FULLA + 8 * p, (ph >> p) & 1);
      {
        const uint32_t src = sb + OFF_RING + p * 32768 + tid * 16;
#pragma unroll
        for (int i = 0; i < 16; i++) {
          float4 v;
          asm volatile("ld.shared.v4.f32 {%0, %1, %2, %3}, [%4];" : "=f"(v.x), "=f"(v.y), "=f"(v.z), "=f"(v.w) : "r"(src + i * 2048));
          acc0[4 * i] += v.x; acc0[4 * i + 1] += v.y; acc0[4 * i + 2] += v.z; acc0[4 * i + 3] += v.w;
        }
      }
      stage_tile(acc0, stg, warp, lane, 1.f);
      p = (p == 4) ? 0 : p + 1;
      mbar_wait(bar + B_FULLA + 8 * p, (ph >> p) & 1);
      {
        const uint32_t src = sb + OFF_RING + p * 32768 + tid * 16;
#pragma unroll
        for (int i = 0; i < 16; i++) {
          float4 v;
          asm volatile("ld.shared.v4.f32 {%0, %1, %2, %3}, [%4];" : "=f"(v.x), "=f"(v.y), "=f"(v.z), "=f"(v.w) : "r"(src + i * 2048));
          acc1[4 * i] += v.x; acc1[4 * i + 1] += v.y; acc1[4 * i + 2] += v.z; acc1[4 * i + 3] += v.w;
        }
      }
      stage_tile(acc1, stg + 16384, warp, lane, 1.f);
      fence_async_smem();
      named_bar<1>();
      if (tid == 0) {
        const int row = rb * 128, col = eb2 * 128;
        tma_store(&P.out, stg, col, row);
        tma_store(&P.out, stg + 8192, col + 64, row);
        tma_store(&P.out, stg + 16384, col, row + 64);
        tma_store(&P.out, stg + 24576, col + 64, row + 64);
        bulk_commit();
        bulk_wait_read();
      }
    }
    __syncwarp();
    cluster_sync();
  } else {
    reg_alloc<160>();
    const int a = wg - 2;
    const uint32_t rel_pred = (lane == 0) && (warp < 2);
    const uint32_t rel_cta = warp & 1;
    const int g = lane >> 2, t = lane & 3;
    {
      float acc[96];
#pragma unroll
      for (int i = 0; i < 96; i++) acc[i] = 0.f;
      fregs(acc);
      for (int e = 0; e < 8; e++) {
        const uint32_t j = e & 3;
        mbar_wait(bar + B_FULLB + 8 * j, (e >> 2) & 1);
        const uint32_t sta = sd + (OFF_RING >> 4) + j * 2560;
        const uint32_t lo = (sta + a * 512) | 0x10000u, lob = (sta + 1024) | (512u << 16);
        wgmma_fence();
#pragma unroll
        for (int kk = 0; kk < 4; kk++) wgmma_ss_n192<1>(acc, desc128(lo + kk * 2), desc128(lob + kk * 128));
        wgmma_commit();
        if (e > 0) {
          wgmma_wait<1>();
          if (rel_pred) mbar_arrive_cluster(bar + B_EMPTYB + 8 * ((e - 1) & 3), rel_cta);
        }
      }
      wgmma_wait<0>();
      fregs(acc);
      if (rel_pred) mbar_arrive_cluster(bar + B_EMPTYB + 8 * 3, rel_cta);
      const uint32_t qs = sb + OFF_QS + a * 8192 + tid * 16;
#pragma unroll
      for (int h = 0; h < 4; h++) {
        asm volatile("st.shared.v4.u32 [%0], {%1, %2, %3, %4};" ::"r"(qs + h * 2048), "r"(pack2(acc[8 * h], acc[8 * h + 1])),
                     "r"(pack2(acc[8 * h + 2], acc[8 * h + 3])), "r"(pack2(acc[8 * h + 4], acc[8 * h + 5])),
                     "r"(pack2(acc[8 * h + 6], acc[8 * h + 7])) : "memory");
      }
      mbar_wait(bar + B_STG, 0);
      const uint32_t stg = sb + OFF_KV + a * 16384;
      {
        const int r = 16 * warp + (lane & 7) + ((lane >> 3) & 1) * 8;
        const uint32_t ad = stg + r * 32 + (((lane >> 4) ^ ((r >> 2) & 1)) << 4);
#pragma unroll
        for (int h = 0; h < 4; h++) {
          stsm4(ad + h * 4096, pack2(acc[32 + 8 * h], acc[32 + 8 * h + 1]), pack2(acc[32 + 8 * h + 2], acc[32 + 8 * h + 3]),
                pack2(acc[32 + 8 * h + 4], acc[32 + 8 * h + 5]), pack2(acc[32 + 8 * h + 6], acc[32 + 8 * h + 7]));
          stsm4(ad + h * 4096 + 2048, pack2(acc[64 + 8 * h], acc[64 + 8 * h + 1]), pack2(acc[64 + 8 * h + 2], acc[64 + 8 * h + 3]),
                pack2(acc[64 + 8 * h + 4], acc[64 + 8 * h + 5]), pack2(acc[64 + 8 * h + 6], acc[64 + 8 * h + 7]));
        }
      }
      fence_async_smem();
      named_bar23(a);
      if (tid == 0) {
#pragma unroll
        for (int h = 0; h < 4; h++)
          bulk_store(g_kv + (size_t)((nb1 * 4 + h) * 32 + 2 * rb + a) * 4096, stg + h * 4096, 4096);
        bulk_commit();
        bulk_wait_all();
        mbar_arrive(bar + B_KVSTG);
        fence_async_all();
        flag_add(g_flags + (F_KV + rb * 8 + nb1) * 32);
      }
      __syncwarp();
    }
    {
      const int lb0 = rb >= 2 ? 0 : 4 - 2 * rb;
      const int base = 2 * t - g - 16 * warp;
      const uint32_t onesw = (sd + (OFF_ONES >> 4)) << 16;
      const uint32_t qs = sb + OFF_QS + a * 8192 + tid * 16;
      __nv_bfloat16* orow = g_o + (size_t)(rb * 128 + a * 64 + warp * 16 + g) * 512 + nb1 * 64 + 2 * t;
      for (int h = 0; h < 4; h++) {
        const int b = h & 1;
        uint32_t q[4];
        asm volatile("ld.shared.v4.u32 {%0, %1, %2, %3}, [%4];" : "=r"(q[0]), "=r"(q[1]), "=r"(q[2]), "=r"(q[3]) : "r"(qs + h * 2048));
        const uint32_t kv = sd + (OFF_KV >> 4) + b * 1536;
        const int lhi = a + 4;
        const bool lov = a >= lb0;
        const int llo = lov ? a : lhi;
        auto kd = [&](int l) -> uint64_t { return desc32((kv + l * 256) | 0x10000u); };
        auto vd = [&](int l) -> uint32_t { return onesw - (kv + l * 256 + 128) * 65535u; };
        float sA[32], sB[32], o[12];
        uint32_t pL[16], pH[16];
        float m0, m1;
        mbar_wait(bar + B_KVFULL + 8 * b, (h >> 1) & 1);
        fregs(q); fregs(sA); fregs(sB);
        wgmma_fence();
        wgmma_rs_n64<0, 0>(sA, q[0], q[1], q[2], q[3], kd(llo));
        wgmma_rs_n64<0, 0>(sB, q[0], q[1], q[2], q[3], kd(lhi));
        wgmma_commit();
        wgmma_wait<0>();
        fregs(sA); fregs(sB);
        if (lov) {
#pragma unroll
          for (int i = 0; i < 32; i++) {
            const int D = (i >> 3) * 16 + ((i >> 2) & 1) * 8 - ((i >> 1) & 1) * 8 + (i & 1);
            sB[i] = (base + D > 0) ? sA[i] : sB[i];
          }
        } else {
#pragma unroll
          for (int i = 0; i < 32; i++) {
            const int D = (i >> 3) * 16 + ((i >> 2) & 1) * 8 - ((i >> 1) & 1) * 8 + (i & 1);
            sB[i] = (base + D > 0) ? -INFINITY : sB[i];
          }
        }
        rowmax(sB, m0, m1);
        exps(sB, -m0 * SC, -m1 * SC, pL);
#pragma unroll
        for (int i = 0; i < 16; i++) {
          const int D = (i >> 2) * 16 + ((i >> 1) & 1) * 8 - (i & 1) * 8;
          const int x = base + D;
          const uint32_t M = x > 0 ? 0xFFFFFFFFu : (x == 0 ? 0xFFFF0000u : 0u);
          pH[i] = pL[i] & ~M; pL[i] &= M;
        }
        fregs(pL); fregs(pH); fregs(o);
        wgmma_fence();
        issue_pv<1>(o, pL, vd(llo));
        issue_pv<0>(o, pH, vd(lhi));
        wgmma_commit();
#pragma unroll
        for (int gi = 1; gi < 4; gi++) {
          const bool val = a + gi >= lb0;
          const int l = val ? a + gi : lhi;
          wgmma_fence();
          wgmma_rs_n64<0, 0>(sA, q[0], q[1], q[2], q[3], kd(l));
          wgmma_commit();
          wgmma_wait<0>();
          fregs(sA); fregs(o);
          const float vb = val ? 0.f : -INFINITY;
          float x0, x1;
          rowmax(sA, x0, x1);
          const float n0 = fmaxf(m0, x0 + vb), n1 = fmaxf(m1, x1 + vb);
          const float al0 = ex2((m0 - n0) * SC), al1 = ex2((m1 - n1) * SC);
          m0 = n0; m1 = n1;
          exps(sA, fmaf(-n0, SC, vb), fmaf(-n1, SC, vb), pL);
#pragma unroll
          for (int i = 0; i < 12; i++) o[i] *= (i & 2) ? al1 : al0;
          fregs(pL); fregs(o);
          wgmma_fence();
          issue_pv<0>(o, pL, vd(l));
          wgmma_commit();
        }
        wgmma_wait<0>();
        fregs(o);
        if (tid == 0) mbar_arrive(bar + B_KVEMPTY + 8 * b);
        const float i0 = rcpf(o[8]), i1 = rcpf(o[10]);
        __nv_bfloat16* op = orow + h * 16;
        *(uint32_t*)(op) = pack2(o[0] * i0, o[1] * i0);
        *(uint32_t*)(op + 8) = pack2(o[4] * i0, o[5] * i0);
        *(uint32_t*)(op + 8 * 512) = pack2(o[2] * i1, o[3] * i1);
        *(uint32_t*)(op + 8 * 512 + 8) = pack2(o[6] * i1, o[7] * i1);
      }
      fence_async_all();
      named_bar23(a);
      if (tid == 0) { flag_add(g_flags + (F_O + rb) * 32); mbar_arrive(bar + B_ATT); }
    }
    if (isY) {
      float acc[64];
#pragma unroll
      for (int i = 0; i < 64; i++) acc[i] = 0.f;
      fregs(acc);
      uint32_t u = 10 + NY;
      uint32_t p = u % 5, pprev = 0;
      uint32_t k5 = u / 5;
      for (int i = 0; i < 8; i++) {
        mbar_wait(bar + B_FULLA + 8 * p, (k5 - (p < 2 ? 1 : 0)) & 1);
        const uint32_t sta = sd + (OFF_RING >> 4) + p * 2048;
        const uint32_t lo = (sta + a * 512) | 0x10000u, lob = (sta + 1024) | (512u << 16);
        wgmma_fence();
#pragma unroll
        for (int kk = 0; kk < 4; kk++) wgmma_ss_n128<1>(acc, desc128(lo + kk * 2), desc128(lob + kk * 128));
        wgmma_commit();
        if (i > 0) {
          wgmma_wait<1>();
          if (rel_pred) mbar_arrive_cluster(bar + B_EMPTYA + 8 * pprev, rel_cta);
        }
        pprev = p;
        if (p == 4) { p = 0; k5++; } else p++;
      }
      wgmma_wait<0>();
      fregs(acc);
      const uint32_t stg = sb + OFF_KV + a * 16384;
      stage_tile(acc, stg, warp, lane, 1.f);
      fence_async_smem();
      named_bar23(a);
      if (tid == 0) {
        const int row = rb * 128 + a * 64, col = 512 + eb2 * 128;
        tma_store(&P.out, stg, col, row);
        tma_store(&P.out, stg + 8192, col + 64, row);
        bulk_commit();
        bulk_wait_read();
      }
    }
    __syncwarp();
    cluster_sync();
  }
}

namespace {
typedef CUresult (*EncodeFn)(CUtensorMap*, CUtensorMapDataType, cuuint32_t, void*, const cuuint64_t*, const cuuint64_t*,
                             const cuuint32_t*, const cuuint32_t*, CUtensorMapInterleave, CUtensorMapSwizzle,
                             CUtensorMapL2promotion, CUtensorMapFloatOOBfill);

void make_map(EncodeFn fn, CUtensorMap* m, const void* ptr, uint64_t cols, uint64_t rows, uint32_t box_cols, uint32_t box_rows) {
  cuuint64_t dims[2] = {cols, rows};
  cuuint64_t strides[1] = {cols * 2};
  cuuint32_t box[2] = {box_cols, box_rows};
  cuuint32_t es[2] = {1, 1};
  fn(m, CU_TENSOR_MAP_DATA_TYPE_BFLOAT16, 2, const_cast<void*>(ptr), dims, strides, box, es, CU_TENSOR_MAP_INTERLEAVE_NONE,
     CU_TENSOR_MAP_SWIZZLE_128B, CU_TENSOR_MAP_L2_PROMOTION_L2_128B, CU_TENSOR_MAP_FLOAT_OOB_FILL_NONE);
}
}

extern "C" void kernel_launch(void* const* d_in, const int* in_sizes, int n_in, void* d_out, int out_size) {
  (void)in_sizes; (void)n_in; (void)out_size;
  static EncodeFn enc = nullptr;
  static void *p_ab = nullptr, *p_o = nullptr;
  if (!enc) {
    void* p = nullptr;
    cudaDriverEntryPointQueryResult st;
    cudaGetDriverEntryPoint("cuTensorMapEncodeTiled", &p, cudaEnableDefault, &st);
    enc = (EncodeFn)p;
    cudaGetSymbolAddress(&p_ab, g_ab);
    cudaGetSymbolAddress(&p_o, g_o);
    cudaFuncSetAttribute(concat_heads__spectral_fnet__sliding_block__prompt_kernel,
                         cudaFuncAttributeMaxDynamicSharedMemorySize, SMEM_BYTES);
  }
  Params P;
  make_map(enc, &P.xa, d_in[0], 512, 2048, 64, 64);
  make_map(enc, &P.cr, d_in[1], 2048, 2048, 64, 64);
  make_map(enc, &P.ci, d_in[2], 2048, 2048, 64, 64);
  make_map(enc, &P.wr, d_in[3], 512, 512, 64, 128);
  make_map(enc, &P.wi, d_in[4], 512, 512, 64, 128);
  make_map(enc, &P.xb, d_in[5], 512, 2048, 64, 64);
  make_map(enc, &P.wqkv, d_in[6], 1536, 512, 64, 64);
  make_map(enc, &P.wo, d_in[7], 512, 512, 64, 64);
  make_map(enc, &P.ab, p_ab, 512, 4096, 64, 64);
  make_map(enc, &P.o, p_o, 512, 2048, 64, 64);
  make_map(enc, &P.out, d_out, 1024, 2048, 64, 64);
  P.p_xa = (const uint8_t*)d_in[0]; P.p_cr = (const uint8_t*)d_in[1]; P.p_ci = (const uint8_t*)d_in[2];
  P.p_wr = (const uint8_t*)d_in[3]; P.p_wi = (const uint8_t*)d_in[4]; P.p_xb = (const uint8_t*)d_in[5];
  P.p_wqkv = (const uint8_t*)d_in[6]; P.p_wo = (const uint8_t*)d_in[7];
  concat_heads__spectral_fnet__sliding_block__prompt_kernel<<<128, 512, SMEM_BYTES>>>(P, (__nv_bfloat16*)d_out);
}
```

```cpp
#include <cuda_runtime.h>
#include <cuda_bf16.h>
#include <cuda.h>
#include <stdint.h>

namespace {

#define NXV 35
constexpr int NX = NXV;
constexpr int NY = 64 - NX;
#define PF_DELAY 1200
constexpr float SC = 0.25f * 1.4426950408889634f;

constexpr uint32_t OFF_RING = 0;
constexpr uint32_t OFF_KV = 163840;
constexpr uint32_t OFF_QS = 212992;
constexpr uint32_t OFF_ONES = 229376;
constexpr uint32_t OFF_BAR = 229888;
constexpr uint32_t OFF_PROF = OFF_BAR + 256;
constexpr uint32_t SMEM_BYTES = OFF_PROF + 1024;
constexpr uint32_t B_FULLA = 0, B_EMPTYA = 40, B_FULLB = 80, B_EMPTYB = 112, B_KVFULL = 144, B_KVEMPTY = 160,
                   B_STG = 176, B_B1END = 184, B_OST = 192, B_PST = 224;
constexpr int N_BARS = 30;

constexpr int F_A = 0, F_KV = 4, F_O = 132, F_P = 196, F_COUNT = 260;

struct __align__(64) Params {
  CUtensorMap xa, wr, wi, xb, wqkv, cr, ci, ab, o, o16, wo4, out;
  const uint8_t* p_xa; const uint8_t* p_wr; const uint8_t* p_wi; const uint8_t* p_xb; const uint8_t* p_wqkv;
  const uint8_t* p_wo; const uint8_t* p_cr; const uint8_t* p_ci;
};

__device__ __align__(1024) __nv_bfloat16 g_ab[4096 * 512];
__device__ __align__(1024) __nv_bfloat16 g_o[2048 * 512];
__device__ __align__(1024) uint8_t g_kv[32 * 32 * 4096];
__device__ __align__(1024) float4 g_part[64 * 32 * 128];
__device__ __align__(1024) unsigned g_flags[F_COUNT * 32];
__device__ __align__(1024) unsigned g_epoch[128 * 32];

#define PROFP(cond, row, slot) do {} while (0)
#define PROFA(k) do {} while (0)
#define PROF(cond, row, slot) do {} while (0)
#define PROFG(cond, idx) do {} while (0)

__device__ __forceinline__ uint32_t smem_u32(const void* p) { return (uint32_t)__cvta_generic_to_shared(p); }
__device__ __forceinline__ void mbar_init(uint32_t bar, uint32_t count) {
  asm volatile("mbarrier.init.shared::cta.b64 [%0], %1;" ::"r"(bar), "r"(count) : "memory");
}
__device__ __forceinline__ void mbar_expect_tx(uint32_t bar, uint32_t bytes) {
  asm volatile("mbarrier.arrive.expect_tx.shared::cta.b64 _, [%0], %1;" ::"r"(bar), "r"(bytes) : "memory");
}
__device__ __forceinline__ void mbar_arrive(uint32_t bar) {
  asm volatile("mbarrier.arrive.shared::cta.b64 _, [%0];" ::"r"(bar) : "memory");
}
__device__ __forceinline__ void mbar_arrive_cluster(uint32_t bar, uint32_t cta) {
  asm volatile("{\n.reg .b32 ra;\nmapa.shared::cluster.u32 ra, %0, %1;\nmbarrier.arrive.shared::cluster.b64 _, [ra];\n}" ::"r"(bar), "r"(cta) : "memory");
}
__device__ __forceinline__ void mbar_wait(uint32_t bar, uint32_t parity) {
  asm volatile("{\n.reg .pred p;\n.reg .u32 c;\nmov.u32 c, 0;\n"
               "LAB_WAIT:\nmbarrier.try_wait.parity.shared::cta.b64 p, [%0], %1;\n@p bra LAB_DONE;\n"
               "add.u32 c, c, 1;\nsetp.lt.u32 p, c, 1048576;\n@p bra LAB_WAIT;\ntrap;\nLAB_DONE:\n}"
               ::"r"(bar), "r"(parity) : "memory");
}
__device__ __forceinline__ void flag_wait(const unsigned* f, unsigned target) {
  asm volatile("{\n.reg .pred p;\n.reg .u32 c, v;\n.reg .s32 d;\nmov.u32 c, 0;\n"
               "LAB_WAIT:\nld.relaxed.gpu.global.u32 v, [%0];\nsub.u32 d, v, %1;\nsetp.ge.s32 p, d, 0;\n"
               "vote.sync.all.pred p, p, 0xffffffff;\n@p bra.uni LAB_DONE;\n"
               "add.u32 c, c, 1;\nsetp.lt.u32 p, c, 1048576;\n@p bra.uni LAB_WAIT;\ntrap;\nLAB_DONE:\nfence.proxy.async.global;\n}"
               ::"l"(f), "r"(target) : "memory");
}
__device__ __forceinline__ void flag_add(unsigned* f) {
  asm volatile("red.relaxed.gpu.global.add.u32 [%0], 1;" ::"l"(f) : "memory");
}
__device__ __forceinline__ void tma_load(uint32_t dst, const CUtensorMap* map, int c0, int c1, uint32_t bar) {
  asm volatile("cp.async.bulk.tensor.2d.shared::cluster.global.mbarrier::complete_tx::bytes [%0], [%1, {%3, %4}], [%2];"
               ::"r"(dst), "l"(map), "r"(bar), "r"(c0), "r"(c1) : "memory");
}
__device__ __forceinline__ void tma_load_mc(uint32_t dst, const CUtensorMap* map, int c0, int c1, uint32_t bar) {
  asm volatile("cp.async.bulk.tensor.2d.shared::cluster.global.mbarrier::complete_tx::bytes.multicast::cluster [%0], [%1, {%3, %4}], [%2], %5;"
               ::"r"(dst), "l"(map), "r"(bar), "r"(c0), "r"(c1), "h"((uint16_t)3) : "memory");
}
__device__ __forceinline__ void tma_load4(uint32_t dst, const CUtensorMap* map, int c0, int c1, int c2, int c3, uint32_t bar) {
  asm volatile("cp.async.bulk.tensor.4d.shared::cluster.global.mbarrier::complete_tx::bytes [%0], [%1, {%3, %4, %5, %6}], [%2];"
               ::"r"(dst), "l"(map), "r"(bar), "r"(c0), "r"(c1), "r"(c2), "r"(c3) : "memory");
}
__device__ __forceinline__ void tma_store(const CUtensorMap* map, uint32_t src, int c0, int c1) {
  asm volatile("cp.async.bulk.tensor.2d.global.shared::cta.bulk_group [%0, {%2, %3}], [%1];"
               ::"l"(map), "r"(src), "r"(c0), "r"(c1) : "memory");
}
__device__ __forceinline__ void bulk_load(uint32_t dst, const void* src, uint32_t bytes, uint32_t bar) {
  asm volatile("cp.async.bulk.shared::cluster.global.mbarrier::complete_tx::bytes [%0], [%1], %2, [%3];"
               ::"r"(dst), "l"(src), "r"(bytes), "r"(bar) : "memory");
}
__device__ __forceinline__ void bulk_store(void* dst, uint32_t src, uint32_t bytes) {
  asm volatile("cp.async.bulk.global.shared::cta.bulk_group [%0], [%1], %2;" ::"l"(dst), "r"(src), "r"(bytes) : "memory");
}
__device__ __forceinline__ void bulk_commit() { asm volatile("cp.async.bulk.commit_group;" ::: "memory"); }
__device__ __forceinline__ void bulk_wait_all() { asm volatile("cp.async.bulk.wait_group 0;" ::: "memory"); }
template <int N> __device__ __forceinline__ void bulk_wait_read() { asm volatile("cp.async.bulk.wait_group.read %0;" ::"n"(N) : "memory"); }
__device__ __forceinline__ void lsu_prefetch(const void* p) { asm volatile("prefetch.global.L2 [%0];" ::"l"(p)); }
__device__ __forceinline__ void l2_prefetch(const void* p, uint32_t bytes) {
  asm volatile("cp.async.bulk.prefetch.L2.global [%0], %1;" ::"l"(p), "r"(bytes) : "memory");
}
__device__ __forceinline__ void map_prefetch(const CUtensorMap* m) {
  asm volatile("prefetch.tensormap [%0];" ::"l"(m) : "memory");
}
__device__ __forceinline__ bool elect_one() {
  uint32_t p;
  asm volatile("{\n.reg .pred P;\nelect.sync _|P, 0xffffffff;\nselp.u32 %0, 1, 0, P;\n}" : "=r"(p));
  return p != 0;
}
__device__ __forceinline__ void cluster_arrive() { asm volatile("barrier.cluster.arrive.relaxed.aligned;" ::: "memory"); }
__device__ __forceinline__ void cluster_wait() { asm volatile("barrier.cluster.wait.aligned;" ::: "memory"); }
template <int ID> __device__ __forceinline__ void named_bar() { asm volatile("bar.sync %0, 128;" ::"n"(ID) : "memory"); }
__device__ __forceinline__ void named_bar23(int a) { if (a == 0) named_bar<2>(); else named_bar<3>(); }
__device__ __forceinline__ void wgmma_fence() { asm volatile("wgmma.fence.sync.aligned;" ::: "memory"); }
__device__ __forceinline__ void wgmma_commit() { asm volatile("wgmma.commit_group.sync.aligned;" ::: "memory"); }
template <int N> __device__ __forceinline__ void wgmma_wait() { asm volatile("wgmma.wait_group.sync.aligned %0;" ::"n"(N) : "memory"); }
template <int R> __device__ __forceinline__ void reg_alloc() { asm volatile("setmaxnreg.inc.sync.aligned.u32 %0;" ::"n"(R)); }
template <int R> __device__ __forceinline__ void reg_dealloc() { asm volatile("setmaxnreg.dec.sync.aligned.u32 %0;" ::"n"(R)); }
__device__ __forceinline__ void fence_async_smem() { asm volatile("fence.proxy.async.shared::cta;" ::: "memory"); }
__device__ __forceinline__ void fence_async_global() { asm volatile("fence.proxy.async.global;" ::: "memory"); }
__device__ __forceinline__ void fence_gpu() { asm volatile("fence.acq_rel.gpu;" ::: "memory"); }
__device__ __forceinline__ float ex2(float x) { float y; asm("ex2.approx.ftz.f32 %0, %1;" : "=f"(y) : "f"(x)); return y; }
__device__ __forceinline__ float rcpf(float x) { float y; asm("rcp.approx.ftz.f32 %0, %1;" : "=f"(y) : "f"(x)); return y; }
__device__ __forceinline__ uint32_t pack2(float lo, float hi) {
  uint32_t r; asm("cvt.rn.bf16x2.f32 %0, %1, %2;" : "=r"(r) : "f"(hi), "f"(lo)); return r;
}
__device__ __forceinline__ void stsm4(uint32_t addr, uint32_t r0, uint32_t r1, uint32_t r2, uint32_t r3) {
  asm volatile("stmatrix.sync.aligned.m8n8.x4.shared.b16 [%0], {%1, %2, %3, %4};" ::"r"(addr), "r"(r0), "r"(r1), "r"(r2), "r"(r3) : "memory");
}
template <int N> __device__ __forceinline__ void fregs(float (&a)[N]) {
#pragma unroll
  for (int i = 0; i < N; i++) asm volatile("" : "+f"(a[i])::"memory");
}
template <int N> __device__ __forceinline__ void fregs(uint32_t (&a)[N]) {
#pragma unroll
  for (int i = 0; i < N; i++) asm volatile("" : "+r"(a[i])::"memory");
}
__device__ __forceinline__ uint64_t desc128(uint32_t lo) { return ((uint64_t)0x40000040u << 32) | lo; }
__device__ __forceinline__ uint64_t desc32(uint32_t lo) { return ((uint64_t)0xC0000010u << 32) | lo; }

template<int TB>
__device__ __forceinline__ void wgmma_ss_n128(float (&d)[64], uint64_t da, uint64_t db, uint32_t accum) {
  asm volatile("{\n.reg .pred p;\nsetp.ne.b32 p, %67, 0;\nwgmma.mma_async.sync.aligned.m64n128k16.f32.bf16.bf16 "
    "{%0, %1, %2, %3, %4, %5, %6, %7, %8, %9, %10, %11, %12, %13, %14, %15, %16, %17, %18, %19, %20, %21, %22, %23, %24, %25, %26, %27, %28, %29, %30, %31, "
    "%32, %33, %34, %35, %36, %37, %38, %39, %40, %41, %42, %43, %44, %45, %46, %47, %48, %49, %50, %51, %52, %53, %54, %55, %56, %57, %58, %59, %60, %61, "
    "%62, %63}"
    ", %64, %65, p, 1, 1, 0, %66;\n}\n"
    :
      "+f"(d[0]), "+f"(d[1]), "+f"(d[2]), "+f"(d[3]), "+f"(d[4]), "+f"(d[5]), "+f"(d[6]), "+f"(d[7]), "+f"(d[8]), "+f"(d[9]), "+f"(d[10]), "+f"(d[11]),
      "+f"(d[12]), "+f"(d[13]), "+f"(d[14]), "+f"(d[15]), "+f"(d[16]), "+f"(d[17]), "+f"(d[18]), "+f"(d[19]), "+f"(d[20]), "+f"(d[21]), "+f"(d[22]),
      "+f"(d[23]), "+f"(d[24]), "+f"(d[25]), "+f"(d[26]), "+f"(d[27]), "+f"(d[28]), "+f"(d[29]), "+f"(d[30]), "+f"(d[31]), "+f"(d[32]), "+f"(d[33]),
      "+f"(d[34]), "+f"(d[35]), "+f"(d[36]), "+f"(d[37]), "+f"(d[38]), "+f"(d[39]), "+f"(d[40]), "+f"(d[41]), "+f"(d[42]), "+f"(d[43]), "+f"(d[44]),
      "+f"(d[45]), "+f"(d[46]), "+f"(d[47]), "+f"(d[48]), "+f"(d[49]), "+f"(d[50]), "+f"(d[51]), "+f"(d[52]), "+f"(d[53]), "+f"(d[54]), "+f"(d[55]),
      "+f"(d[56]), "+f"(d[57]), "+f"(d[58]), "+f"(d[59]), "+f"(d[60]), "+f"(d[61]), "+f"(d[62]), "+f"(d[63])
    : "l"(da), "l"(db), "n"(TB), "r"(accum));
}

template<int TB>
__device__ __forceinline__ void wgmma_ss_n192(float (&d)[96], uint64_t da, uint64_t db, uint32_t accum) {
  asm volatile("{\n.reg .pred p;\nsetp.ne.b32 p, %99, 0;\nwgmma.mma_async.sync.aligned.m64n192k16.f32.bf16.bf16 "
    "{%0, %1, %2, %3, %4, %5, %6, %7, %8, %9, %10, %11, %12, %13, %14, %15, %16, %17, %18, %19, %20, %21, %22, %23, %24, %25, %26, %27, %28, %29, %30, %31, "
    "%32, %33, %34, %35, %36, %37, %38, %39, %40, %41, %42, %43, %44, %45, %46, %47, %48, %49, %50, %51, %52, %53, %54, %55, %56, %57, %58, %59, %60, %61, "
    "%62, %63, %64, %65, %66, %67, %68, %69, %70, %71, %72, %73, %74, %75, %76, %77, %78, %79, %80, %81, %82, %83, %84, %85, %86, %87, %88, %89, %90, %91, "
    "%92, %93, %94, %95}"
    ", %96, %97, p, 1, 1, 0, %98;\n}\n"
    :
      "+f"(d[0]), "+f"(d[1]), "+f"(d[2]), "+f"(d[3]), "+f"(d[4]), "+f"(d[5]), "+f"(d[6]), "+f"(d[7]), "+f"(d[8]), "+f"(d[9]), "+f"(d[10]), "+f"(d[11]),
      "+f"(d[12]), "+f"(d[13]), "+f"(d[14]), "+f"(d[15]), "+f"(d[16]), "+f"(d[17]), "+f"(d[18]), "+f"(d[19]), "+f"(d[20]), "+f"(d[21]), "+f"(d[22]),
      "+f"(d[23]), "+f"(d[24]), "+f"(d[25]), "+f"(d[26]), "+f"(d[27]), "+f"(d[28]), "+f"(d[29]), "+f"(d[30]), "+f"(d[31]), "+f"(d[32]), "+f"(d[33]),
      "+f"(d[34]), "+f"(d[35]), "+f"(d[36]), "+f"(d[37]), "+f"(d[38]), "+f"(d[39]), "+f"(d[40]), "+f"(d[41]), "+f"(d[42]), "+f"(d[43]), "+f"(d[44]),
      "+f"(d[45]), "+f"(d[46]), "+f"(d[47]), "+f"(d[48]), "+f"(d[49]), "+f"(d[50]), "+f"(d[51]), "+f"(d[52]), "+f"(d[53]), "+f"(d[54]), "+f"(d[55]),
      "+f"(d[56]), "+f"(d[57]), "+f"(d[58]), "+f"(d[59]), "+f"(d[60]), "+f"(d[61]), "+f"(d[62]), "+f"(d[63]), "+f"(d[64]), "+f"(d[65]), "+f"(d[66]),
      "+f"(d[67]), "+f"(d[68]), "+f"(d[69]), "+f"(d[70]), "+f"(d[71]), "+f"(d[72]), "+f"(d[73]), "+f"(d[74]), "+f"(d[75]), "+f"(d[76]), "+f"(d[77]),
      "+f"(d[78]), "+f"(d[79]), "+f"(d[80]), "+f"(d[81]), "+f"(d[82]), "+f"(d[83]), "+f"(d[84]), "+f"(d[85]), "+f"(d[86]), "+f"(d[87]), "+f"(d[88]),
      "+f"(d[89]), "+f"(d[90]), "+f"(d[91]), "+f"(d[92]), "+f"(d[93]), "+f"(d[94]), "+f"(d[95])
    : "l"(da), "l"(db), "n"(TB), "r"(accum));
}

template<int TB, int ACC>
__device__ __forceinline__ void wgmma_rs_n64(float (&d)[32], uint32_t a0, uint32_t a1, uint32_t a2, uint32_t a3, uint64_t db) {
  asm volatile("{\n.reg .pred p;\nsetp.ne.b32 p, %38, 0;\nwgmma.mma_async.sync.aligned.m64n64k16.f32.bf16.bf16 "
    "{%0, %1, %2, %3, %4, %5, %6, %7, %8, %9, %10, %11, %12, %13, %14, %15, %16, %17, %18, %19, %20, %21, %22, %23, %24, %25, %26, %27, %28, %29, %30, %31}"
    ", {%32, %33, %34, %35}, %36, p, 1, 1, %37;\n}\n"
    :
      "+f"(d[0]), "+f"(d[1]), "+f"(d[2]), "+f"(d[3]), "+f"(d[4]), "+f"(d[5]), "+f"(d[6]), "+f"(d[7]), "+f"(d[8]), "+f"(d[9]), "+f"(d[10]), "+f"(d[11]),
      "+f"(d[12]), "+f"(d[13]), "+f"(d[14]), "+f"(d[15]), "+f"(d[16]), "+f"(d[17]), "+f"(d[18]), "+f"(d[19]), "+f"(d[20]), "+f"(d[21]), "+f"(d[22]),
      "+f"(d[23]), "+f"(d[24]), "+f"(d[25]), "+f"(d[26]), "+f"(d[27]), "+f"(d[28]), "+f"(d[29]), "+f"(d[30]), "+f"(d[31])
    : "r"(a0), "r"(a1), "r"(a2), "r"(a3), "l"(db), "n"(TB), "n"(ACC));
}

template<int TB, int ACC>
__device__ __forceinline__ void wgmma_rs_n24(float (&d)[12], uint32_t a0, uint32_t a1, uint32_t a2, uint32_t a3, uint64_t db) {
  asm volatile("{\n.reg .pred p;\nsetp.ne.b32 p, %18, 0;\nwgmma.mma_async.sync.aligned.m64n24k16.f32.bf16.bf16 "
    "{%0, %1, %2, %3, %4, %5, %6, %7, %8, %9, %10, %11}"
    ", {%12, %13, %14, %15}, %16, p, 1, 1, %17;\n}\n"
    :
      "+f"(d[0]), "+f"(d[1]), "+f"(d[2]), "+f"(d[3]), "+f"(d[4]), "+f"(d[5]), "+f"(d[6]), "+f"(d[7]), "+f"(d[8]), "+f"(d[9]), "+f"(d[10]), "+f"(d[11])
    : "r"(a0), "r"(a1), "r"(a2), "r"(a3), "l"(db), "n"(TB), "n"(ACC));
}

__device__ __forceinline__ void stage_tile(const float (&d)[64], uint32_t stg, int w, int lane, uint32_t sgn) {
  const int r = 16 * w + (lane & 7) + ((lane >> 3) & 1) * 8;
  const uint32_t rowa = stg + r * 128;
  const int hi = lane >> 4, sw = r & 7;
#pragma unroll
  for (int jj = 0; jj < 8; jj++) {
    const int chunk = 2 * (jj & 3) + hi;
    const uint32_t addr = rowa + (jj >> 2) * 8192 + ((chunk ^ sw) << 4);
    stsm4(addr, pack2(d[8 * jj], d[8 * jj + 1]) ^ sgn, pack2(d[8 * jj + 2], d[8 * jj + 3]) ^ sgn,
          pack2(d[8 * jj + 4], d[8 * jj + 5]) ^ sgn, pack2(d[8 * jj + 6], d[8 * jj + 7]) ^ sgn);
  }
}

__device__ __forceinline__ void rowmax(const float (&s)[32], float& x0, float& x1) {
  float a0 = fmaxf(s[0], s[1]), a1 = fmaxf(s[2], s[3]), b0 = fmaxf(s[4], s[5]), b1 = fmaxf(s[6], s[7]);
#pragma unroll
  for (int i = 8; i < 32; i += 8) {
    a0 = fmaxf(a0, fmaxf(s[i], s[i + 1])); a1 = fmaxf(a1, fmaxf(s[i + 2], s[i + 3]));
    b0 = fmaxf(b0, fmaxf(s[i + 4], s[i + 5])); b1 = fmaxf(b1, fmaxf(s[i + 6], s[i + 7]));
  }
  x0 = fmaxf(a0, b0); x1 = fmaxf(a1, b1);
  x0 = fmaxf(x0, __shfl_xor_sync(~0u, x0, 1)); x1 = fmaxf(x1, __shfl_xor_sync(~0u, x1, 1));
  x0 = fmaxf(x0, __shfl_xor_sync(~0u, x0, 2)); x1 = fmaxf(x1, __shfl_xor_sync(~0u, x1, 2));
}
__device__ __forceinline__ void exps(float (&s)[32], float mc0, float mc1) {
#pragma unroll
  for (int i = 0; i < 32; i++) s[i] = ex2(fmaf(s[i], SC, (i & 2) ? mc1 : mc0));
}
__device__ __forceinline__ void packp(const float (&s)[32], uint32_t (&p)[16]) {
#pragma unroll
  for (int i = 0; i < 16; i++) p[i] = pack2(s[2 * i], s[2 * i + 1]);
}
template <int FIRST>
__device__ __forceinline__ void issue_pv(float (&o)[12], const uint32_t (&p)[16], uint32_t vlo) {
#pragma unroll
  for (int c = 0; c < 4; c++) {
    const uint64_t d = desc32(vlo - (uint32_t)c * (32u * 65535u));
    if (FIRST && c == 0) wgmma_rs_n24<1, 0>(o, p[0], p[1], p[2], p[3], d);
    else wgmma_rs_n24<1, 1>(o, p[c * 4 + 0], p[c * 4 + 1], p[c * 4 + 2], p[c * 4 + 3], d);
  }
}

}

#define GEMM_KBLOCK(first, RELEASE)                                                                     \
  do {                                                                                                   \
    const uint32_t sta_ = sd + (OFF_RING >> 4) + p * 2048;                                               \
    const uint32_t lo_ = sta_ | 0x10000u, lob_ = (sta_ + 1024) | (512u << 16);                           \
    wgmma_fence();                                                                                       \
    _Pragma("unroll") for (int kk = 0; kk < 4; kk++) {                                                   \
      const uint64_t db_ = desc128(lob_ + kk * 128);                                                     \
      const uint32_t ac_ = kk > 0 ? 1u : (uint32_t)!(first);                                             \
      wgmma_ss_n128<1>(acc0, desc128(lo_ + kk * 2), db_, ac_);                                           \
      wgmma_ss_n128<1>(acc1, desc128(lo_ + 512 + kk * 2), db_, ac_);                                     \
      wgmma_commit();                                                                                    \
      wgmma_wait<1>();                                                                                   \
      if (kk == 0 && (RELEASE) && rel_pred) mbar_arrive_cluster(bar + B_EMPTYA + 8 * pprev, rel_cta);    \
    }                                                                                                    \
  } while (0)

__global__ void __cluster_dims__(2, 1, 1) __launch_bounds__(512, 1)
concat_heads__spectral_fnet__sliding_block__prompt_kernel(const __grid_constant__ Params P) {
  extern __shared__ uint8_t smem_raw[];
  const uint32_t sb = (smem_u32(smem_raw) + 1023) & ~1023u;
  const uint32_t bar = sb + OFF_BAR;
  const uint32_t sd = (sb & 0x3FFFFu) >> 4;
  const int wg = __shfl_sync(~0u, threadIdx.x >> 7, 0);
  const int warp = __shfl_sync(~0u, (threadIdx.x >> 5) & 3, 0);
  const int lane = threadIdx.x & 31;
  const int tid = threadIdx.x & 127;
  const int rank = blockIdx.x & 1;
  const int cl = blockIdx.x >> 1;
  const int rb = cl >> 2;
  const int q4 = cl & 3;
  const int isY = q4 & 1;
  const int cp = q4 >> 1;
  const int eb2 = 2 * cp + rank;
  const int nb1 = 2 * q4 + rank;
  const int tile = rb * 4 + eb2;

  if (threadIdx.x < 32) {
    if (lane < N_BARS) {
      const uint32_t cnt = lane < 5 ? 1 : lane < 10 ? 4 : lane < 14 ? 1 : lane < 18 ? 4 : lane < 20 ? 1 : lane < 22 ? 2
                         : lane == 22 ? 1 : lane == 23 ? 2 : lane < 28 ? 8 : 4;
      mbar_init(bar + 8 * lane, cnt);
    }
    asm volatile("fence.mbarrier_init.release.cluster;" ::: "memory");
    fence_async_smem();
  } else if (threadIdx.x < 64) {
    if (lane < 12) map_prefetch(&P.xa + lane);
  } else if (wg >= 2) {
    asm volatile("st.shared.u32 [%0], %1;" ::"r"(sb + OFF_ONES + tid * 4), "r"(0x3f803f80u) : "memory");
  }
  cluster_arrive();
  cluster_wait();
  PROF(tid == 0, wg, 1);

  if (wg == 0) {
    reg_dealloc<24>();
    unsigned ep = 0;
    if (warp < 2) asm volatile("ld.relaxed.gpu.global.u32 %0, [%1];" : "=r"(ep) : "l"(g_epoch + blockIdx.x * 32));
    if (warp == 0) {
      uint32_t useA = 0;
      uint32_t p = 2;
      const int arow = rb * 128 + rank * 64;
      {
        const CUtensorMap* mw = (nb1 & 4) ? &P.wi : &P.wr;
#pragma unroll 1
        for (int n = 0; n < 8; n++) {
          if (n >= 5) { mbar_wait(bar + B_EMPTYA + 8 * p, ((useA >> p) & 1) ^ 1); __syncwarp(); }
          const uint32_t st = sb + OFF_RING + p * 32768, fb = bar + B_FULLA + 8 * p;
          if (elect_one()) {
            mbar_expect_tx(fb, 32768);
            tma_load_mc(st + rank * 8192, &P.xa, n * 64, arow, fb);
            tma_load(st + 16384, mw, n * 64, (nb1 & 3) * 128, fb);
          }
          PROF(lane == 0 && n == 0, 0, 22); PROF(lane == 0 && n == 4, 0, 23); PROF(lane == 0 && n == 5, 0, 24);
          useA ^= 1u << p;
          p = (p == 4) ? 0 : p + 1;
        }
      }
      PROF(lane == 0, 0, 2);
#pragma unroll 1
      for (int e = 0; e < 8; e++) {
        const uint32_t j = e & 3;
        if (e < 4) mbar_wait(bar + B_EMPTYA + 8 * (e + 1), ((useA >> (e + 1)) & 1) ^ 1);
        else mbar_wait(bar + B_EMPTYB + 8 * j, 0);
        __syncwarp();
        const uint32_t wb = sb + OFF_RING + (j < 2 ? j * 40960 : 98304 + (j - 2) * 32768);
        const uint32_t xa = rank == 0 ? wb + 24576 : (j < 2 ? wb + 32768 : sb + OFF_KV + 32768 + (j - 2) * 8192);
        const uint32_t fb = bar + B_FULLB + 8 * j;
        if (elect_one()) {
          mbar_expect_tx(fb, 40960);
          tma_load_mc(xa, &P.xb, e * 64, arow, fb);
          tma_load(wb, &P.wqkv, nb1 * 64, e * 64, fb);
          tma_load(wb + 8192, &P.wqkv, 512 + nb1 * 64, e * 64, fb);
          tma_load(wb + 16384, &P.wqkv, 1024 + nb1 * 64, e * 64, fb);
        }
      }
      PROF(lane == 0, 0, 3);
      p = 0;
      {
        const int kb0 = isY ? NX : 0, nk = isY ? NY : NX;
#pragma unroll 1
        for (int m = 0; m < nk; m++) {
          mbar_wait(bar + B_EMPTYA + 8 * p, ((useA >> p) & 1) ^ 1);
          if (m < 5) mbar_wait(bar + B_EMPTYB + 8 * (m == 0 ? 0 : (m <= 2 ? 1 : m - 1)), 1);
          __syncwarp();
          PROFP(lane == 0, 7, m);
          const int kb = kb0 + m;
          const uint32_t st = sb + OFF_RING + p * 32768, fb = bar + B_FULLA + 8 * p;
          if (elect_one()) {
            mbar_expect_tx(fb, 32768);
            tma_load_mc(st + rank * 8192, kb < 32 ? &P.cr : &P.ci, (kb & 31) * 64, arow, fb);
          }
          if (m == 0) { PROF(lane == 0, 0, 4); flag_wait(g_flags + (F_A + eb2) * 32, (ep + 1) * 32); PROF(lane == 0, 0, 5); }
          if (elect_one()) {
            tma_load(st + 16384, &P.ab, eb2 * 128, kb * 64, fb);
            tma_load(st + 24576, &P.ab, eb2 * 128 + 64, kb * 64, fb);
          }
          PROFP(lane == 0, 6, m);
          useA ^= 1u << p;
          p = (p == 4) ? 0 : p + 1;
        }
      }
      PROF(lane == 0, 0, 6);
      if (isY) {
#pragma unroll 1
        for (int i = 0; i < 8; i++) {
          mbar_wait(bar + B_EMPTYA + 8 * p, ((useA >> p) & 1) ^ 1);
          __syncwarp();
          const uint32_t st = sb + OFF_RING + p * 32768, fb = bar + B_FULLA + 8 * p;
          if (elect_one()) {
            mbar_expect_tx(fb, 32768);
            tma_load4(st + 16384, &P.wo4, eb2 * 128, 0, i >> 1, (i & 1) * 4, fb);
            tma_load4(st + 24576, &P.wo4, eb2 * 128 + 64, 0, i >> 1, (i & 1) * 4, fb);
          }
          if ((i & 1) == 0) {
            PROF(lane == 0, 0, 7 + (i >> 1) * 2);
            flag_wait(g_flags + (F_O + rb * 4 + (i >> 1)) * 32, (ep + 1) * 8);
            PROF(lane == 0, 0, 8 + (i >> 1) * 2);
          }
          if (elect_one()) tma_load_mc(st + rank * 8192, &P.o, i * 64, arow, fb);
          useA ^= 1u << p;
          p = (p == 4) ? 0 : p + 1;
        }
      } else {
#pragma unroll 1
        for (int i = 0; i < 2; i++) {
          mbar_wait(bar + B_EMPTYA + 8 * p, ((useA >> p) & 1) ^ 1);
          __syncwarp();
          if (i == 0) { PROF(lane == 0, 0, 7); flag_wait(g_flags + (F_P + tile) * 32, ep + 1); PROF(lane == 0, 0, 8); }
          const uint32_t fb = bar + B_FULLA + 8 * p;
          if (elect_one()) {
            mbar_expect_tx(fb, 32768);
            bulk_load(sb + OFF_RING + p * 32768, g_part + (size_t)tile * 4096 + i * 2048, 32768, fb);
          }
          useA ^= 1u << p;
          p = (p == 4) ? 0 : p + 1;
        }
      }
      PROF(lane == 0, 0, 15);
    } else if (warp == 1) {
      const int lb0 = rb >= 2 ? 0 : 4 - 2 * rb;
      mbar_wait(bar + B_B1END, 0);
      __syncwarp();
      PROF(lane == 0, 4, 2);
      {
        int r = rb - (lane % 3);
        r = r < 0 ? 0 : r;
        flag_wait(g_flags + (F_KV + r * 8 + nb1) * 32, (ep + 1) * 2);
      }
      PROF(lane == 0, 4, 3);
#pragma unroll 1
      for (int h = 0; h < 4; h++) {
        const int b = h & 1;
        if (h >= 2) { mbar_wait(bar + B_KVEMPTY + 8 * b, 0); __syncwarp(); }
        const uint32_t bytes = (6 - lb0) * 4096;
        if (elect_one()) {
          mbar_expect_tx(bar + B_KVFULL + 8 * b, bytes);
          bulk_load(sb + OFF_KV + b * 24576 + lb0 * 4096, g_kv + (size_t)((nb1 * 4 + h) * 32 + 2 * rb - 4 + lb0) * 4096, bytes,
                    bar + B_KVFULL + 8 * b);
        }
        PROF(lane == 0, 4, 4 + h);
      }
      if (isY) {
        const uint32_t p0 = (NY - 2) % 5, p1 = (NY - 1) % 5;
        mbar_wait(bar + B_PST, 0);
        __syncwarp();
        if (lane == 0) { bulk_store(g_part + (size_t)tile * 4096, sb + OFF_RING + p0 * 32768, 32768); bulk_commit(); }
        mbar_wait(bar + B_PST + 8, 0);
        __syncwarp();
        PROF(lane == 0, 4, 8);
        if (lane == 0) { bulk_store(g_part + (size_t)tile * 4096 + 2048, sb + OFF_RING + p1 * 32768, 32768); bulk_commit(); bulk_wait_read<1>(); }
        __syncwarp();
        if (lane < 4) mbar_arrive_cluster(bar + B_EMPTYA + 8 * p0, lane & 1);
        if (lane == 0) bulk_wait_read<0>();
        __syncwarp();
        if (lane < 4) mbar_arrive_cluster(bar + B_EMPTYA + 8 * p1, lane & 1);
        PROF(lane == 0, 4, 9);
        if (lane == 0) { bulk_wait_all(); flag_add(g_flags + (F_P + tile) * 32); }
        PROF(lane == 0, 4, 10);
      }
    } else if (warp == 2) {
#pragma unroll 1
      for (int h = 0; h < 4; h++) {
        mbar_wait(bar + B_OST + 8 * h, 0);
        __syncwarp();
        if (lane == 0) {
          tma_store(&P.o16, sb + OFF_QS + h * 4096, h * 128 + nb1 * 16, rb * 128);
          bulk_commit();
          bulk_wait_all();
          flag_add(g_flags + (F_O + rb * 4 + h) * 32);
        }
        PROF(lane == 0, 4, 12 + h);
      }
    } else {
    }
    __syncwarp();
    cluster_arrive();
    cluster_wait();
    if (threadIdx.x == 0) g_epoch[blockIdx.x * 32] = ep + 1;
  } else if (wg == 1) {
    reg_alloc<168>();
    float acc0[64], acc1[64];
    uint32_t ph = 0, p = 2;
    const uint32_t rel_pred = (lane == 0);
    const uint32_t rel_cta = warp & 1;
#pragma unroll
    for (int i = 0; i < 64; i++) { acc0[i] = 0.f; acc1[i] = 0.f; }
    fregs(acc0); fregs(acc1);
    uint32_t pprev = 0;
#pragma unroll 1
    for (int n = 0; n < 8; n++) {
      mbar_wait(bar + B_FULLA + 8 * p, (ph >> p) & 1);
      PROF(tid == 0 && n == 0, 1, 2);
      ph ^= 1u << p;
      const uint32_t lo = (sd + (OFF_RING >> 4) + p * 2048) | 0x10000u;
      wgmma_fence();
#pragma unroll
      for (int kk = 0; kk < 4; kk++) {
        const uint64_t db = desc128(lo + 1024 + kk * 2);
        wgmma_ss_n128<0>(acc0, desc128(lo + kk * 2), db, 1);
        wgmma_ss_n128<0>(acc1, desc128(lo + 512 + kk * 2), db, 1);
      }
      wgmma_commit();
      if (n > 0) {
        wgmma_wait<1>();
        if (rel_pred) mbar_arrive_cluster(bar + B_EMPTYA + 8 * pprev, rel_cta);
      }
      pprev = p;
      p = (p == 4) ? 0 : p + 1;
    }
    wgmma_wait<0>();
    fregs(acc0); fregs(acc1);
    if (rel_pred) mbar_arrive_cluster(bar + B_EMPTYA + 8 * pprev, rel_cta);
    PROF(tid == 0, 1, 3);
    {
      const uint32_t sgn = (nb1 & 4) ? 0x80008000u : 0u;
      const uint32_t stg = sb + OFF_KV;
      stage_tile(acc0, stg, warp, lane, sgn);
      stage_tile(acc1, stg + 16384, warp, lane, sgn);
      PROF(tid == 0, 1, 22);
      fence_async_smem();
      named_bar<1>();
      if (tid == 0) {
        const int row = (nb1 >> 2) * 2048 + rb * 128, col = (nb1 & 3) * 128;
        tma_store(&P.ab, stg, col, row);
        tma_store(&P.ab, stg + 8192, col + 64, row);
        tma_store(&P.ab, stg + 16384, col, row + 64);
        tma_store(&P.ab, stg + 24576, col + 64, row + 64);
        bulk_commit();
        PROF(true, 1, 24);
        bulk_wait_all();
        flag_add(g_flags + (F_A + (nb1 & 3)) * 32);
        mbar_arrive(bar + B_STG);
        PROF(true, 1, 4);
      }
      __syncwarp();
    }
    p = 0;
    const int nk = isY ? NY : NX;
    const int nrel = isY ? NY - 1 : NX;
    mbar_wait(bar + B_B1END, 0);
#pragma unroll 1
    for (int m = 0; m < nk; m++) {
      mbar_wait(bar + B_FULLA + 8 * p, (ph >> p) & 1);
      PROF(tid == 0, 5, m);
      ph ^= 1u << p;
      GEMM_KBLOCK(m == 0, m > 0 && m < nrel);
      pprev = p;
      p = (p == 4) ? 0 : p + 1;
    }
    wgmma_wait<0>();
    fregs(acc0); fregs(acc1);
    PROF(tid == 0, 1, 7);
    if (isY) {
      {
        const uint32_t d0 = sb + OFF_RING + ((NY - 2) % 5) * 32768 + tid * 16, d1 = sb + OFF_RING + ((NY - 1) % 5) * 32768 + tid * 16;
#pragma unroll
        for (int i = 0; i < 16; i++)
          asm volatile("st.shared.v4.f32 [%0], {%1, %2, %3, %4};" ::"r"(d0 + i * 2048), "f"(acc0[4 * i]), "f"(acc0[4 * i + 1]), "f"(acc0[4 * i + 2]), "f"(acc0[4 * i + 3]) : "memory");
        fence_async_smem();
        __syncwarp();
        if (lane == 0) mbar_arrive(bar + B_PST);
#pragma unroll
        for (int i = 0; i < 16; i++)
          asm volatile("st.shared.v4.f32 [%0], {%1, %2, %3, %4};" ::"r"(d1 + i * 2048), "f"(acc1[4 * i]), "f"(acc1[4 * i + 1]), "f"(acc1[4 * i + 2]), "f"(acc1[4 * i + 3]) : "memory");
        fence_async_smem();
        __syncwarp();
        if (lane == 0) mbar_arrive(bar + B_PST + 8);
      }
      PROF(tid == 0, 1, 8);
#pragma unroll 1
      for (int i = 0; i < 8; i++) {
        mbar_wait(bar + B_FULLA + 8 * p, (ph >> p) & 1);
        PROF(tid == 0, 1, 11 + i);
        ph ^= 1u << p;
        GEMM_KBLOCK(i == 0, i > 0 && i < 4);
        pprev = p;
        p = (p == 4) ? 0 : p + 1;
      }
      wgmma_wait<0>();
      fregs(acc0); fregs(acc1);
      PROF(tid == 0, 1, 9);
      const uint32_t stg = sb + OFF_RING + p * 32768;
      const int row = rb * 128, col = 512 + eb2 * 128;
      stage_tile(acc0, stg, warp, lane, 0);
      fence_async_smem();
      named_bar<1>();
      if (tid == 0) { tma_store(&P.out, stg, col, row); tma_store(&P.out, stg + 8192, col + 64, row); bulk_commit(); }
      stage_tile(acc1, stg + 16384, warp, lane, 0);
      fence_async_smem();
      named_bar<1>();
      if (tid == 0) {
        tma_store(&P.out, stg + 16384, col, row + 64);
        tma_store(&P.out, stg + 24576, col + 64, row + 64);
        bulk_commit();
        bulk_wait_read<0>();
      }
    } else {
      const uint32_t p1 = (p == 4) ? 0 : p + 1, p2 = (p1 == 4) ? 0 : p1 + 1;
      const uint32_t stg = sb + OFF_RING + p2 * 32768;
      const int row = rb * 128, col = eb2 * 128;
      mbar_wait(bar + B_FULLA + 8 * p, (ph >> p) & 1);
      PROF(tid == 0, 1, 8);
      {
        const uint32_t src = sb + OFF_RING + p * 32768 + tid * 16;
#pragma unroll
        for (int i = 0; i < 16; i++) {
          float4 v;
          asm volatile("ld.shared.v4.f32 {%0, %1, %2, %3}, [%4];" : "=f"(v.x), "=f"(v.y), "=f"(v.z), "=f"(v.w) : "r"(src + i * 2048));
          acc0[4 * i] += v.x; acc0[4 * i + 1] += v.y; acc0[4 * i + 2] += v.z; acc0[4 * i + 3] += v.w;
        }
      }
      stage_tile(acc0, stg, warp, lane, 0);
      fence_async_smem();
      named_bar<1>();
      if (tid == 0) { tma_store(&P.out, stg, col, row); tma_store(&P.out, stg + 8192, col + 64, row); bulk_commit(); }
      mbar_wait(bar + B_FULLA + 8 * p1, (ph >> p1) & 1);
      {
        const uint32_t src = sb + OFF_RING + p1 * 32768 + tid * 16;
#pragma unroll
        for (int i = 0; i < 16; i++) {
          float4 v;
          asm volatile("ld.shared.v4.f32 {%0, %1, %2, %3}, [%4];" : "=f"(v.x), "=f"(v.y), "=f"(v.z), "=f"(v.w) : "r"(src + i * 2048));
          acc1[4 * i] += v.x; acc1[4 * i + 1] += v.y; acc1[4 * i + 2] += v.z; acc1[4 * i + 3] += v.w;
        }
      }
      stage_tile(acc1, stg + 16384, warp, lane, 0);
      fence_async_smem();
      named_bar<1>();
      if (tid == 0) {
        tma_store(&P.out, stg + 16384, col, row + 64);
        tma_store(&P.out, stg + 24576, col + 64, row + 64);
        bulk_commit();
        bulk_wait_read<0>();
      }
    }
    PROF(tid == 0, 1, 10);
    __syncwarp();
    cluster_arrive();
    cluster_wait();
  } else {
    reg_alloc<160>();
    const int a = wg - 2;
    const int g = lane >> 2, t = lane & 3;
    const uint32_t qs = sb + OFF_QS + a * 2048 + tid * 16;
    {
      const uint32_t rel_pred = (lane == 0) && (warp < 2);
      const uint32_t rel_cta = warp & 1;
      float acc[96];
#pragma unroll
      for (int i = 0; i < 96; i++) acc[i] = 0.f;
      fregs(acc);
#pragma unroll 1
      for (int e = 0; e < 8; e++) {
        const uint32_t j = e & 3;
        mbar_wait(bar + B_FULLB + 8 * j, (e >> 2) & 1);
        PROF(tid == 0 && e == 0, wg, 2);
        const uint32_t wb = (j < 2 ? j * 40960 : 98304 + (j - 2) * 32768);
        const uint32_t xa = a == 0 ? wb + 24576 : (j < 2 ? wb + 32768 : OFF_KV + 32768 + (j - 2) * 8192);
        const uint32_t lo = (sd + (xa >> 4)) | 0x10000u, lob = (sd + (wb >> 4)) | (512u << 16);
        wgmma_fence();
#pragma unroll
        for (int kk = 0; kk < 4; kk++) wgmma_ss_n192<1>(acc, desc128(lo + kk * 2), desc128(lob + kk * 128), 1);
        wgmma_commit();
        if (e == 7 && tid == 0) mbar_arrive(bar + B_B1END);
        if (e > 0) {
          wgmma_wait<1>();
          if (rel_pred) mbar_arrive_cluster(bar + B_EMPTYB + 8 * ((e - 1) & 3), rel_cta);
        }
      }
      wgmma_wait<0>();
      fregs(acc);
      if (rel_pred) mbar_arrive_cluster(bar + B_EMPTYB + 8 * 3, rel_cta);
      PROF(tid == 0, wg, 3);
      mbar_wait(bar + B_STG, 0);
      const uint32_t stg = sb + OFF_KV + a * 16384;
      {
        const int r = 16 * warp + (lane & 7) + ((lane >> 3) & 1) * 8;
        const uint32_t ad = stg + r * 32 + (((lane >> 4) ^ ((r >> 2) & 1)) << 4);
#pragma unroll
        for (int h = 0; h < 4; h++) {
          stsm4(ad + h * 4096, pack2(acc[32 + 8 * h], acc[32 + 8 * h + 1]), pack2(acc[32 + 8 * h + 2], acc[32 + 8 * h + 3]),
                pack2(acc[32 + 8 * h + 4], acc[32 + 8 * h + 5]), pack2(acc[32 + 8 * h + 6], acc[32 + 8 * h + 7]));
          stsm4(ad + h * 4096 + 2048, pack2(acc[64 + 8 * h], acc[64 + 8 * h + 1]), pack2(acc[64 + 8 * h + 2], acc[64 + 8 * h + 3]),
                pack2(acc[64 + 8 * h + 4], acc[64 + 8 * h + 5]), pack2(acc[64 + 8 * h + 6], acc[64 + 8 * h + 7]));
        }
      }
      fence_async_smem();
      named_bar23(a);
      if (tid == 0) {
#pragma unroll
        for (int h = 0; h < 4; h++)
          bulk_store(g_kv + (size_t)((nb1 * 4 + h) * 32 + 2 * rb + a) * 4096, stg + h * 4096, 4096);
        bulk_commit();
        PROF(true, wg, 22);
      }
#pragma unroll
      for (int h = 0; h < 4; h++) {
        asm volatile("st.shared.v4.u32 [%0], {%1, %2, %3, %4};" ::"r"(qs + h * 4096), "r"(pack2(acc[8 * h], acc[8 * h + 1])),
                     "r"(pack2(acc[8 * h + 2], acc[8 * h + 3])), "r"(pack2(acc[8 * h + 4], acc[8 * h + 5])),
                     "r"(pack2(acc[8 * h + 6], acc[8 * h + 7])) : "memory");
      }
      if (tid == 0) {
        bulk_wait_all();
        flag_add(g_flags + (F_KV + rb * 8 + nb1) * 32);
        PROF(true, wg, 5);
      }
      __syncwarp();
    }
    {
      const int lb0 = rb >= 2 ? 0 : 4 - 2 * rb;
      const int base = 2 * t - g - 16 * warp;
      const uint32_t onesw = (sd + (OFF_ONES >> 4)) << 16;
      const int lhi = a + 4;
      const bool lov = a >= lb0;
      const int llo = lov ? a : lhi;
      const int l1 = a + 1 >= lb0 ? a + 1 : lhi, l2 = a + 2 >= lb0 ? a + 2 : lhi, l3 = a + 3 >= lb0 ? a + 3 : lhi;
      const float vb1 = a + 1 >= lb0 ? 0.f : -INFINITY, vb2 = a + 2 >= lb0 ? 0.f : -INFINITY, vb3 = a + 3 >= lb0 ? 0.f : -INFINITY;
      const uint32_t ost = sb + OFF_QS + a * 2048 + warp * 512 + ((lane & 7) + ((lane >> 3) & 1) * 8) * 32 + (lane >> 4) * 16;
      const uint32_t kv0 = sd + (OFF_KV >> 4);
      float sA[32], sB[32], o[12];
      uint32_t pL[16], pH[16], q[4];
      float m0, m1;
#define KD(kv, l) desc32(((kv) + (l) * 256) | 0x10000u)
#define VD(kv, l) (onesw - ((kv) + (l) * 256 + 128) * 65535u)
#define FINALIZE(hh)                                                                                     \
      do {                                                                                               \
        const float i0 = rcpf(o[8]), i1 = rcpf(o[10]);                                                   \
        stsm4(ost + (hh) * 4096, pack2(o[0] * i0, o[1] * i0), pack2(o[2] * i1, o[3] * i1),               \
              pack2(o[4] * i0, o[5] * i0), pack2(o[6] * i1, o[7] * i1));                                 \
        fence_async_smem();                                                                              \
        __syncwarp();                                                                                    \
        if (lane == 0) mbar_arrive(bar + B_OST + 8 * (hh));                                              \
      } while (0)
#define SOFT_STEP(s, vb)                                                                                 \
        float x0, x1;                                                                                    \
        rowmax(s, x0, x1);                                                                               \
        const float n0 = fmaxf(m0, x0 + (vb)), n1 = fmaxf(m1, x1 + (vb));                                \
        const float al0 = ex2((m0 - n0) * SC), al1 = ex2((m1 - n1) * SC);                                \
        m0 = n0; m1 = n1;                                                                                \
        exps(s, fmaf(-n0, SC, vb), fmaf(-n1, SC, vb));
#define RESCALE() _Pragma("unroll") for (int i = 0; i < 12; i++) o[i] *= (i & 2) ? al1 : al0;

#pragma unroll
      for (int i = 0; i < 12; i++) o[i] = 0.f;
      asm volatile("ld.shared.v4.u32 {%0, %1, %2, %3}, [%4];" : "=r"(q[0]), "=r"(q[1]), "=r"(q[2]), "=r"(q[3]) : "r"(qs));
      mbar_wait(bar + B_KVFULL, 0);
      PROF(tid == 0, wg, 6);
      fregs(q); fregs(sA); fregs(sB); fregs(o);
      wgmma_fence();
      wgmma_rs_n64<0, 0>(sB, q[0], q[1], q[2], q[3], KD(kv0, lhi));
      wgmma_rs_n64<0, 0>(sA, q[0], q[1], q[2], q[3], KD(kv0, llo));
      wgmma_commit();
      wgmma_commit();
#pragma unroll 1
      for (int h = 0; h < 4; h++) {
        const uint32_t kv = kv0 + (h & 1) * 1536;
        wgmma_wait<1>();
        fregs(sA); fregs(sB);
        PROFA(0);
        if (lov) {
#pragma unroll
          for (int i = 0; i < 32; i++) {
            const int D = (i >> 3) * 16 + ((i >> 2) & 1) * 8 - ((i >> 1) & 1) * 8 + (i & 1);
            sB[i] = (base + D > 0) ? sA[i] : sB[i];
          }
        } else {
#pragma unroll
          for (int i = 0; i < 32; i++) {
            const int D = (i >> 3) * 16 + ((i >> 2) & 1) * 8 - ((i >> 1) & 1) * 8 + (i & 1);
            sB[i] = (base + D > 0) ? -INFINITY : sB[i];
          }
        }
        fregs(sA); fregs(sB);
        wgmma_fence();
        wgmma_rs_n64<0, 0>(sA, q[0], q[1], q[2], q[3], KD(kv, l1));
        wgmma_commit();
        PROFA(1);
        rowmax(sB, m0, m1);
        exps(sB, -m0 * SC, -m1 * SC);
        fregs(sB);
        PROFA(2);
        wgmma_wait<1>();
        fregs(o);
        PROFA(3);
        if (h > 0) {
          if (tid == 0 && h < 3) mbar_arrive(bar + B_KVEMPTY + 8 * ((h - 1) & 1));
          FINALIZE(h - 1);
          PROF(tid == 0, wg, 10 + h - 1);
        }
        packp(sB, pL);
#pragma unroll
        for (int i = 0; i < 16; i++) {
          const int D = (i >> 2) * 16 + ((i >> 1) & 1) * 8 - (i & 1) * 8;
          const int x = base + D;
          const uint32_t M = x > 0 ? 0xFFFFFFFFu : (x == 0 ? 0xFFFF0000u : 0u);
          pH[i] = pL[i] & ~M; pL[i] &= M;
        }
        fregs(pL); fregs(pH); fregs(o); fregs(sB);
        wgmma_fence();
        issue_pv<1>(o, pL, VD(kv, llo));
        PROFA(4);
        issue_pv<0>(o, pH, VD(kv, lhi));
        wgmma_commit();
        PROFA(5);
        {
          wgmma_wait<1>();
          PROFA(6);
          fregs(sA); fregs(sB);
          wgmma_fence();
          wgmma_rs_n64<0, 0>(sB, q[0], q[1], q[2], q[3], KD(kv, l2));
          wgmma_commit();
          PROFA(7);
          SOFT_STEP(sA, vb1);
          fregs(sA);
          PROFA(8);
          wgmma_wait<1>();
          PROFA(9);
          fregs(o); fregs(pL); fregs(pH);
          RESCALE();
          packp(sA, pL);
          fregs(pL); fregs(o); fregs(sA);
          wgmma_fence();
          PROFA(10);
          issue_pv<0>(o, pL, VD(kv, l1));
          wgmma_commit();
          PROFA(11);
        }
        {
          wgmma_wait<1>();
          PROFA(12);
          fregs(sA); fregs(sB);
          wgmma_fence();
          wgmma_rs_n64<0, 0>(sA, q[0], q[1], q[2], q[3], KD(kv, l3));
          wgmma_commit();
          PROFA(13);
          SOFT_STEP(sB, vb2);
          fregs(sB);
          PROFA(14);
          wgmma_wait<1>();
          PROFA(15);
          fregs(o); fregs(pL);
          RESCALE();
          packp(sB, pL);
          fregs(pL); fregs(o); fregs(sB);
          wgmma_fence();
          PROFA(16);
          issue_pv<0>(o, pL, VD(kv, l2));
          wgmma_commit();
          PROFA(17);
        }
        {
          const uint32_t kvn = kv0 + ((h + 1) & 1) * 1536;
          wgmma_wait<1>();
          PROFA(18);
          fregs(sA); fregs(sB); fregs(q);
          if (h < 3) mbar_wait(bar + B_KVFULL + 8 * ((h + 1) & 1), ((h + 1) >> 1) & 1);
          PROF(tid == 0 && h < 3, wg, 7 + h);
          asm volatile("ld.shared.v4.u32 {%0, %1, %2, %3}, [%4];" : "=r"(q[0]), "=r"(q[1]), "=r"(q[2]), "=r"(q[3]) : "r"(qs + ((h + 1) & 3) * 4096));
          fregs(q);
          wgmma_fence();
          wgmma_rs_n64<0, 0>(sB, q[0], q[1], q[2], q[3], KD(kvn, lhi));
          wgmma_commit();
          PROFA(19);
          SOFT_STEP(sA, vb3);
          fregs(sA);
          PROFA(20);
          wgmma_wait<1>();
          PROFA(21);
          fregs(o); fregs(pL);
          RESCALE();
          packp(sA, pL);
          fregs(pL); fregs(o); fregs(sA);
          wgmma_fence();
          wgmma_rs_n64<0, 0>(sA, q[0], q[1], q[2], q[3], KD(kvn, llo));
          wgmma_commit();
          PROFA(22);
          issue_pv<0>(o, pL, VD(kv, l3));
          wgmma_commit();
          PROFA(23);
        }
      }
      wgmma_wait<0>();
      fregs(o); fregs(sA); fregs(sB);
      FINALIZE(3);
      PROF(tid == 0, wg, 13);
    }
    PROF(tid == 0, wg, 17);
    __syncwarp();
    cluster_arrive();
    cluster_wait();
  }
}

namespace {
typedef CUresult (*EncodeFn)(CUtensorMap*, CUtensorMapDataType, cuuint32_t, void*, const cuuint64_t*, const cuuint64_t*,
                             const cuuint32_t*, const cuuint32_t*, CUtensorMapInterleave, CUtensorMapSwizzle,
                             CUtensorMapL2promotion, CUtensorMapFloatOOBfill);

void make_map(EncodeFn fn, CUtensorMap* m, const void* ptr, uint64_t cols, uint64_t rows, uint32_t box_cols, uint32_t box_rows,
              CUtensorMapSwizzle sw = CU_TENSOR_MAP_SWIZZLE_128B) {
  cuuint64_t dims[2] = {cols, rows};
  cuuint64_t strides[1] = {cols * 2};
  cuuint32_t box[2] = {box_cols, box_rows};
  cuuint32_t es[2] = {1, 1};
  fn(m, CU_TENSOR_MAP_DATA_TYPE_BFLOAT16, 2, const_cast<void*>(ptr), dims, strides, box, es, CU_TENSOR_MAP_INTERLEAVE_NONE,
     sw, CU_TENSOR_MAP_L2_PROMOTION_L2_128B, CU_TENSOR_MAP_FLOAT_OOB_FILL_NONE);
}
}

extern "C" void kernel_launch(void* const* d_in, const int* in_sizes, int n_in, void* d_out, int out_size) {
  (void)in_sizes; (void)n_in; (void)out_size;
  static EncodeFn enc = nullptr;
  static void *p_ab = nullptr, *p_o = nullptr;
  if (!enc) {
    void* p = nullptr;
    cudaDriverEntryPointQueryResult st;
    cudaGetDriverEntryPoint("cuTensorMapEncodeTiled", &p, cudaEnableDefault, &st);
    enc = (EncodeFn)p;
    cudaGetSymbolAddress(&p_ab, g_ab);
    cudaGetSymbolAddress(&p_o, g_o);
    cudaFuncSetAttribute(concat_heads__spectral_fnet__sliding_block__prompt_kernel,
                         cudaFuncAttributeMaxDynamicSharedMemorySize, SMEM_BYTES);
  }
  Params P;
  make_map(enc, &P.xa, d_in[0], 512, 2048, 64, 64);
  make_map(enc, &P.cr, d_in[1], 2048, 2048, 64, 64);
  make_map(enc, &P.ci, d_in[2], 2048, 2048, 64, 64);
  make_map(enc, &P.wr, d_in[3], 512, 512, 64, 128);
  make_map(enc, &P.wi, d_in[4], 512, 512, 64, 128);
  make_map(enc, &P.xb, d_in[5], 512, 2048, 64, 64);
  make_map(enc, &P.wqkv, d_in[6], 1536, 512, 64, 64);
  {
    cuuint64_t dims[4] = {512, 16, 4, 8};
    cuuint64_t strides[3] = {1024, 16 * 1024, 64 * 1024};
    cuuint32_t box[4] = {64, 16, 1, 4};
    cuuint32_t es[4] = {1, 1, 1, 1};
    enc(&P.wo4, CU_TENSOR_MAP_DATA_TYPE_BFLOAT16, 4, d_in[7], dims, strides, box, es, CU_TENSOR_MAP_INTERLEAVE_NONE,
        CU_TENSOR_MAP_SWIZZLE_128B, CU_TENSOR_MAP_L2_PROMOTION_L2_128B, CU_TENSOR_MAP_FLOAT_OOB_FILL_NONE);
  }
  make_map(enc, &P.ab, p_ab, 512, 4096, 64, 64);
  make_map(enc, &P.o, p_o, 512, 2048, 64, 64);
  make_map(enc, &P.o16, p_o, 512, 2048, 16, 128, CU_TENSOR_MAP_SWIZZLE_NONE);
  make_map(enc, &P.out, d_out, 1024, 2048, 64, 64);
  P.p_xa = (const uint8_t*)d_in[0]; P.p_cr = (const uint8_t*)d_in[1]; P.p_ci = (const uint8_t*)d_in[2];
  P.p_wr = (const uint8_t*)d_in[3]; P.p_wi = (const uint8_t*)d_in[4]; P.p_xb = (const uint8_t*)d_in[5];
  P.p_wqkv = (const uint8_t*)d_in[6]; P.p_wo = (const uint8_t*)d_in[7];
  concat_heads__spectral_fnet__sliding_block__prompt_kernel<<<128, 512, SMEM_BYTES>>>(P);
}
```

```cpp
#include <cuda_runtime.h>
#include <cuda_bf16.h>
#include <cuda.h>
#include <stdint.h>

namespace {

constexpr int NX = 36;
constexpr int NY = 64 - NX;
constexpr int PSD = 4, PSD2 = 6;

constexpr float SC = 0.25f * 1.4426950408889634f;
#define ATT_LMAX 4.2535296e37f
constexpr float ATT_OFF = 16.f;

constexpr uint32_t OFF_RING = 0;
constexpr uint32_t OFF_KV = 163840;
constexpr uint32_t OFF_QS = 212992;
constexpr uint32_t OFF_ONES = 229376;
constexpr uint32_t OFF_BAR = 229888;
constexpr uint32_t SMEM_BYTES = OFF_BAR + 320 + 1024;
constexpr uint32_t B_FULLA = 0, B_EMPTYA = 40, B_FULLB = 80, B_EMPTYB = 112, B_KVFULL = 144, B_KVEMPTY = 160,
                   B_ARD = 176, B_B1END = 184, B_OST = 192, B_PST = 224, B_AST = 240, B_ORDY = 256, B_A1I = 288, B_M4I = 296, B_ARD2 = 304, B_MSK = 312;
constexpr uint64_t BAR_CNT_LO = 0x4411114444411111ull, BAR_CNT_HI = 0x4444888821881144ull;

constexpr int F_A = 0, F_KV = 128, F_O = 256, F_P = 320, F_COUNT = 384;

struct __align__(64) Params {
  unsigned* flags; unsigned* epoch; uint8_t* kv;
  uint8_t* ab; const uint8_t* p_wo;
  const uint8_t* p_xb; const uint8_t* p_wq;
  uint64_t pad[1];
  const uint8_t* p_xa; const uint8_t* p_wr; const uint8_t* p_wi; const uint8_t* p_cr; const uint8_t* p_ci;
  uint64_t pad2[3];
  CUtensorMap xb, wqkv, xa, wr, wi, cr, ci, o, o16, wo4, out;
};

__device__ __align__(1024) uint8_t g_ab[64 * 4 * 16384];
__device__ __align__(1024) __nv_bfloat16 g_o[2048 * 512];
__device__ __align__(1024) uint8_t g_kv[32 * 32 * 4096];
__device__ __align__(1024) unsigned g_flags[F_COUNT * 32];
__device__ __align__(1024) unsigned g_epoch[128 * 32];

__device__ __forceinline__ uint32_t smem_u32(const void* p) { return (uint32_t)__cvta_generic_to_shared(p); }
__device__ __forceinline__ void mbar_init(uint32_t bar, uint32_t count) {
  asm volatile("mbarrier.init.shared::cta.b64 [%0], %1;" ::"r"(bar), "r"(count) : "memory");
}
__device__ __forceinline__ void mbar_expect_tx(uint32_t bar, uint32_t bytes) {
  asm volatile("mbarrier.arrive.expect_tx.shared::cta.b64 _, [%0], %1;" ::"r"(bar), "r"(bytes) : "memory");
}
__device__ __forceinline__ void mbar_arrive(uint32_t bar) {
  asm volatile("mbarrier.arrive.shared::cta.b64 _, [%0];" ::"r"(bar) : "memory");
}
__device__ __forceinline__ void mbar_arrive_cluster(uint32_t bar, uint32_t cta) {
  asm volatile("{\n.reg .b32 ra;\nmapa.shared::cluster.u32 ra, %0, %1;\nmbarrier.arrive.shared::cluster.b64 _, [ra];\n}" ::"r"(bar), "r"(cta) : "memory");
}
__device__ __forceinline__ void mbar_wait(uint32_t bar, uint32_t parity) {
  asm volatile("{\n.reg .pred p;\n.reg .u32 c;\nmov.u32 c, 0;\n"
               "LAB_WAIT:\nmbarrier.try_wait.parity.shared::cta.b64 p, [%0], %1;\n@p bra LAB_DONE;\n"
               "add.u32 c, c, 1;\nsetp.lt.u32 p, c, 1048576;\n@p bra LAB_WAIT;\ntrap;\nLAB_DONE:\n}"
               ::"r"(bar), "r"(parity) : "memory");
}
__device__ __forceinline__ void flag_wait(const unsigned* f, unsigned target) {
  asm volatile("{\n.reg .pred p;\n.reg .u32 c, v;\n.reg .s32 d;\nmov.u32 c, 0;\n"
               "LAB_WAIT:\nld.relaxed.gpu.global.u32 v, [%0];\nsub.u32 d, v, %1;\nsetp.ge.s32 p, d, 0;\n"
               "vote.sync.all.pred p, p, 0xffffffff;\n@p bra.uni LAB_DONE;\n"
               "add.u32 c, c, 1;\nsetp.lt.u32 p, c, 1048576;\n@p bra.uni LAB_WAIT;\ntrap;\nLAB_DONE:\nfence.proxy.async.global;\n}"
               ::"l"(f), "r"(target) : "memory");
}
__device__ __forceinline__ void flag_watch(const unsigned* f, unsigned target, uint32_t need, uint32_t msk, uint32_t lane0) {
  asm volatile("{\n.reg .pred p, q;\n.reg .u32 c, v, m0, m1, l0, l1, t, u;\n.reg .s32 d;\nmov.u32 c, 0;\nmov.u32 l0, 0;\nmov.u32 l1, 0;\n"
               "setp.ne.u32 q, %4, 0;\n"
               "LAB_WAIT:\nld.relaxed.gpu.global.u32 v, [%0];\nsub.u32 d, v, %1;\nsetp.ge.s32 p, d, 0;\n"
               "vote.sync.ballot.b32 m0, p, 0xffffffff;\nsetp.ge.s32 p, d, 1;\nvote.sync.ballot.b32 m1, p, 0xffffffff;\n"
               "xor.b32 t, m0, l0;\nxor.b32 u, m1, l1;\nor.b32 t, t, u;\nsetp.eq.u32 p, t, 0;\n@p bra.uni LAB_SAME;\n"
               "fence.proxy.async.global;\n@q st.release.cta.shared.u32 [%3], m0;\n@q st.release.cta.shared.u32 [%3 + 4], m1;\n"
               "mov.u32 l0, m0;\nmov.u32 l1, m1;\n"
               "and.b32 t, m1, %2;\nsetp.eq.u32 p, t, %2;\n@p bra.uni LAB_DONE;\n"
               "LAB_SAME:\nadd.u32 c, c, 1;\nsetp.lt.u32 p, c, 1048576;\n@p bra.uni LAB_WAIT;\ntrap;\nLAB_DONE:\n}"
               ::"l"(f), "r"(target), "r"(need), "r"(msk), "r"(lane0) : "memory");
}
__device__ __forceinline__ uint32_t smem_mask_wait(uint32_t addr, uint32_t bit) {
  uint32_t m;
  asm volatile("{\n.reg .pred p;\n.reg .u32 c, t;\nmov.u32 c, 0;\n"
               "LAB_WAIT:\nld.acquire.cta.shared.u32 %0, [%1];\nand.b32 t, %0, %2;\nsetp.ne.u32 p, t, 0;\n@p bra.uni LAB_DONE;\n"
               "add.u32 c, c, 1;\nsetp.lt.u32 p, c, 16777216;\n@p bra.uni LAB_WAIT;\ntrap;\nLAB_DONE:\n}"
               : "=r"(m) : "r"(addr), "r"(bit) : "memory");
  return m;
}
__device__ __forceinline__ bool is_eq(int x, int v) {
  uint32_t p;
  asm volatile("{\n.reg .pred P;\nsetp.eq.s32 P, %1, %2;\nselp.u32 %0, 1, 0, P;\n}" : "=r"(p) : "r"(x), "r"(v));
  return p != 0;
}
__device__ __forceinline__ void flag_add(unsigned* f) {
  asm volatile("red.relaxed.gpu.global.add.u32 [%0], 1;" ::"l"(f) : "memory");
}
__device__ __forceinline__ void tma_load(uint32_t dst, const CUtensorMap* map, int c0, int c1, uint32_t bar) {
  asm volatile("cp.async.bulk.tensor.2d.shared::cluster.global.mbarrier::complete_tx::bytes [%0], [%1, {%3, %4}], [%2];"
               ::"r"(dst), "l"(map), "r"(bar), "r"(c0), "r"(c1) : "memory");
}
__device__ __forceinline__ void tma_load_mc(uint32_t dst, const CUtensorMap* map, int c0, int c1, uint32_t bar) {
  asm volatile("cp.async.bulk.tensor.2d.shared::cluster.global.mbarrier::complete_tx::bytes.multicast::cluster [%0], [%1, {%3, %4}], [%2], %5;"
               ::"r"(dst), "l"(map), "r"(bar), "r"(c0), "r"(c1), "h"((uint16_t)3) : "memory");
}
__device__ __forceinline__ void tma_load4(uint32_t dst, const CUtensorMap* map, int c0, int c1, int c2, int c3, uint32_t bar) {
  asm volatile("cp.async.bulk.tensor.4d.shared::cluster.global.mbarrier::complete_tx::bytes [%0], [%1, {%3, %4, %5, %6}], [%2];"
               ::"r"(dst), "l"(map), "r"(bar), "r"(c0), "r"(c1), "r"(c2), "r"(c3) : "memory");
}
__device__ __forceinline__ void tma_store(const CUtensorMap* map, uint32_t src, int c0, int c1) {
  asm volatile("cp.async.bulk.tensor.2d.global.shared::cta.bulk_group [%0, {%2, %3}], [%1];"
               ::"l"(map), "r"(src), "r"(c0), "r"(c1) : "memory");
}
__device__ __forceinline__ void tma_red_add(const CUtensorMap* map, uint32_t src, int c0, int c1) {
  asm volatile("cp.reduce.async.bulk.tensor.2d.global.shared::cta.add.tile.bulk_group [%0, {%2, %3}], [%1];"
               ::"l"(map), "r"(src), "r"(c0), "r"(c1) : "memory");
}
__device__ __forceinline__ void bulk_load(uint32_t dst, const void* src, uint32_t bytes, uint32_t bar) {
  asm volatile("cp.async.bulk.shared::cluster.global.mbarrier::complete_tx::bytes [%0], [%1], %2, [%3];"
               ::"r"(dst), "l"(src), "r"(bytes), "r"(bar) : "memory");
}
__device__ __forceinline__ void bulk_store(void* dst, uint32_t src, uint32_t bytes) {
  asm volatile("cp.async.bulk.global.shared::cta.bulk_group [%0], [%1], %2;" ::"l"(dst), "r"(src), "r"(bytes) : "memory");
}
__device__ __forceinline__ void bulk_commit() { asm volatile("cp.async.bulk.commit_group;" ::: "memory"); }
__device__ __forceinline__ void bulk_wait_all() { asm volatile("cp.async.bulk.wait_group 0;" ::: "memory"); }
template <int N> __device__ __forceinline__ void bulk_wait_read() { asm volatile("cp.async.bulk.wait_group.read %0;" ::"n"(N) : "memory"); }
__device__ __forceinline__ void lsu_prefetch(const void* p) { asm volatile("prefetch.global.L2 [%0];" ::"l"(p)); }
__device__ __forceinline__ void map_prefetch(const CUtensorMap* m) {
  asm volatile("prefetch.tensormap [%0];" ::"l"(m) : "memory");
}
__device__ __forceinline__ bool elect_one() {
  uint32_t p;
  asm volatile("{\n.reg .pred P;\nelect.sync _|P, 0xffffffff;\nselp.u32 %0, 1, 0, P;\n}" : "=r"(p));
  return p != 0;
}
__device__ __forceinline__ void cluster_arrive() { asm volatile("barrier.cluster.arrive.relaxed.aligned;" ::: "memory"); }
__device__ __forceinline__ void cluster_wait() { asm volatile("barrier.cluster.wait.aligned;" ::: "memory"); }
template <int ID> __device__ __forceinline__ void named_bar() { asm volatile("bar.sync %0, 128;" ::"n"(ID) : "memory"); }
__device__ __forceinline__ void named_bar23(int a) { if (a == 0) named_bar<2>(); else named_bar<3>(); }
__device__ __forceinline__ void wgmma_fence() { asm volatile("wgmma.fence.sync.aligned;" ::: "memory"); }
__device__ __forceinline__ void wgmma_commit() { asm volatile("wgmma.commit_group.sync.aligned;" ::: "memory"); }
template <int N> __device__ __forceinline__ void wgmma_wait() { asm volatile("wgmma.wait_group.sync.aligned %0;" ::"n"(N) : "memory"); }
__device__ __forceinline__ bool bar_red_or(bool v) {
  uint32_t r;
  asm volatile("{\n.reg .pred p, q;\nsetp.ne.u32 q, %1, 0;\nbar.red.or.pred p, 5, 256, q;\nselp.u32 %0, 1, 0, p;\n}" : "=r"(r) : "r"((uint32_t)v) : "memory");
  return r != 0;
}
template <int R> __device__ __forceinline__ void reg_alloc() { asm volatile("setmaxnreg.inc.sync.aligned.u32 %0;" ::"n"(R)); }
template <int R> __device__ __forceinline__ void reg_dealloc() { asm volatile("setmaxnreg.dec.sync.aligned.u32 %0;" ::"n"(R)); }
__device__ __forceinline__ void fence_async_smem() { asm volatile("fence.proxy.async.shared::cta;" ::: "memory"); }
__device__ __forceinline__ float ex2(float x) { float y; asm("ex2.approx.ftz.f32 %0, %1;" : "=f"(y) : "f"(x)); return y; }
__device__ __forceinline__ float rcpf(float x) { float y; asm("rcp.approx.ftz.f32 %0, %1;" : "=f"(y) : "f"(x)); return y; }
__device__ __forceinline__ uint32_t pack2(float lo, float hi) {
  uint32_t r; asm("cvt.rn.bf16x2.f32 %0, %1, %2;" : "=r"(r) : "f"(hi), "f"(lo)); return r;
}
__device__ __forceinline__ void stsm4(uint32_t addr, uint32_t r0, uint32_t r1, uint32_t r2, uint32_t r3) {
  asm volatile("stmatrix.sync.aligned.m8n8.x4.shared.b16 [%0], {%1, %2, %3, %4};" ::"r"(addr), "r"(r0), "r"(r1), "r"(r2), "r"(r3) : "memory");
}
template <int N> __device__ __forceinline__ void fregs(float (&a)[N]) {
#pragma unroll
  for (int i = 0; i < N; i++) asm volatile("" : "+f"(a[i])::"memory");
}
template <int N> __device__ __forceinline__ void fregs(uint32_t (&a)[N]) {
#pragma unroll
  for (int i = 0; i < N; i++) asm volatile("" : "+r"(a[i])::"memory");
}
__device__ __forceinline__ uint64_t desc128(uint32_t lo) { return ((uint64_t)0x40000040u << 32) | lo; }
__device__ __forceinline__ uint64_t desc32(uint32_t lo) { return ((uint64_t)0xC0000010u << 32) | lo; }

template<int TB>
__device__ __forceinline__ void wgmma_ss_n128(float (&d)[64], uint64_t da, uint64_t db, uint32_t accum) {
  asm volatile("{\n.reg .pred p;\nsetp.ne.b32 p, %67, 0;\nwgmma.mma_async.sync.aligned.m64n128k16.f32.bf16.bf16 "
    "{%0, %1, %2, %3, %4, %5, %6, %7, %8, %9, %10, %11, %12, %13, %14, %15, %16, %17, %18, %19, %20, %21, %22, %23, %24, %25, %26, %27, %28, %29, %30, %31, "
    "%32, %33, %34, %35, %36, %37, %38, %39, %40, %41, %42, %43, %44, %45, %46, %47, %48, %49, %50, %51, %52, %53, %54, %55, %56, %57, %58, %59, %60, %61, "
    "%62, %63}"
    ", %64, %65, p, 1, 1, 0, %66;\n}\n"
    :
      "+f"(d[0]), "+f"(d[1]), "+f"(d[2]), "+f"(d[3]), "+f"(d[4]), "+f"(d[5]), "+f"(d[6]), "+f"(d[7]), "+f"(d[8]), "+f"(d[9]), "+f"(d[10]), "+f"(d[11]),
      "+f"(d[12]), "+f"(d[13]), "+f"(d[14]), "+f"(d[15]), "+f"(d[16]), "+f"(d[17]), "+f"(d[18]), "+f"(d[19]), "+f"(d[20]), "+f"(d[21]), "+f"(d[22]),
      "+f"(d[23]), "+f"(d[24]), "+f"(d[25]), "+f"(d[26]), "+f"(d[27]), "+f"(d[28]), "+f"(d[29]), "+f"(d[30]), "+f"(d[31]), "+f"(d[32]), "+f"(d[33]),
      "+f"(d[34]), "+f"(d[35]), "+f"(d[36]), "+f"(d[37]), "+f"(d[38]), "+f"(d[39]), "+f"(d[40]), "+f"(d[41]), "+f"(d[42]), "+f"(d[43]), "+f"(d[44]),
      "+f"(d[45]), "+f"(d[46]), "+f"(d[47]), "+f"(d[48]), "+f"(d[49]), "+f"(d[50]), "+f"(d[51]), "+f"(d[52]), "+f"(d[53]), "+f"(d[54]), "+f"(d[55]),
      "+f"(d[56]), "+f"(d[57]), "+f"(d[58]), "+f"(d[59]), "+f"(d[60]), "+f"(d[61]), "+f"(d[62]), "+f"(d[63])
    : "l"(da), "l"(db), "n"(TB), "r"(accum));
}

template<int TB>
__device__ __forceinline__ void wgmma_ss_n192(float (&d)[96], uint64_t da, uint64_t db, uint32_t accum) {
  asm volatile("{\n.reg .pred p;\nsetp.ne.b32 p, %99, 0;\nwgmma.mma_async.sync.aligned.m64n192k16.f32.bf16.bf16 "
    "{%0, %1, %2, %3, %4, %5, %6, %7, %8, %9, %10, %11, %12, %13, %14, %15, %16, %17, %18, %19, %20, %21, %22, %23, %24, %25, %26, %27, %28, %29, %30, %31, "
    "%32, %33, %34, %35, %36, %37, %38, %39, %40, %41, %42, %43, %44, %45, %46, %47, %48, %49, %50, %51, %52, %53, %54, %55, %56, %57, %58, %59, %60, %61, "
    "%62, %63, %64, %65, %66, %67, %68, %69, %70, %71, %72, %73, %74, %75, %76, %77, %78, %79, %80, %81, %82, %83, %84, %85, %86, %87, %88, %89, %90, %91, "
    "%92, %93, %94, %95}"
    ", %96, %97, p, 1, 1, 0, %98;\n}\n"
    :
      "+f"(d[0]), "+f"(d[1]), "+f"(d[2]), "+f"(d[3]), "+f"(d[4]), "+f"(d[5]), "+f"(d[6]), "+f"(d[7]), "+f"(d[8]), "+f"(d[9]), "+f"(d[10]), "+f"(d[11]),
      "+f"(d[12]), "+f"(d[13]), "+f"(d[14]), "+f"(d[15]), "+f"(d[16]), "+f"(d[17]), "+f"(d[18]), "+f"(d[19]), "+f"(d[20]), "+f"(d[21]), "+f"(d[22]),
      "+f"(d[23]), "+f"(d[24]), "+f"(d[25]), "+f"(d[26]), "+f"(d[27]), "+f"(d[28]), "+f"(d[29]), "+f"(d[30]), "+f"(d[31]), "+f"(d[32]), "+f"(d[33]),
      "+f"(d[34]), "+f"(d[35]), "+f"(d[36]), "+f"(d[37]), "+f"(d[38]), "+f"(d[39]), "+f"(d[40]), "+f"(d[41]), "+f"(d[42]), "+f"(d[43]), "+f"(d[44]),
      "+f"(d[45]), "+f"(d[46]), "+f"(d[47]), "+f"(d[48]), "+f"(d[49]), "+f"(d[50]), "+f"(d[51]), "+f"(d[52]), "+f"(d[53]), "+f"(d[54]), "+f"(d[55]),
      "+f"(d[56]), "+f"(d[57]), "+f"(d[58]), "+f"(d[59]), "+f"(d[60]), "+f"(d[61]), "+f"(d[62]), "+f"(d[63]), "+f"(d[64]), "+f"(d[65]), "+f"(d[66]),
      "+f"(d[67]), "+f"(d[68]), "+f"(d[69]), "+f"(d[70]), "+f"(d[71]), "+f"(d[72]), "+f"(d[73]), "+f"(d[74]), "+f"(d[75]), "+f"(d[76]), "+f"(d[77]),
      "+f"(d[78]), "+f"(d[79]), "+f"(d[80]), "+f"(d[81]), "+f"(d[82]), "+f"(d[83]), "+f"(d[84]), "+f"(d[85]), "+f"(d[86]), "+f"(d[87]), "+f"(d[88]),
      "+f"(d[89]), "+f"(d[90]), "+f"(d[91]), "+f"(d[92]), "+f"(d[93]), "+f"(d[94]), "+f"(d[95])
    : "l"(da), "l"(db), "n"(TB), "r"(accum));
}

template<int TB, int ACC>
__device__ __forceinline__ void wgmma_rs_n24(float (&d)[12], uint32_t a0, uint32_t a1, uint32_t a2, uint32_t a3, uint64_t db) {
  asm volatile("{\n.reg .pred p;\nsetp.ne.b32 p, %18, 0;\nwgmma.mma_async.sync.aligned.m64n24k16.f32.bf16.bf16 "
    "{%0, %1, %2, %3, %4, %5, %6, %7, %8, %9, %10, %11}"
    ", {%12, %13, %14, %15}, %16, p, 1, 1, %17;\n}\n"
    :
      "+f"(d[0]), "+f"(d[1]), "+f"(d[2]), "+f"(d[3]), "+f"(d[4]), "+f"(d[5]), "+f"(d[6]), "+f"(d[7]), "+f"(d[8]), "+f"(d[9]), "+f"(d[10]), "+f"(d[11])
    : "r"(a0), "r"(a1), "r"(a2), "r"(a3), "l"(db), "n"(TB), "n"(ACC));
}

template<int TB, int OFF>
__device__ __forceinline__ void wgmma_rs_n32(float (&d)[32], uint32_t a0, uint32_t a1, uint32_t a2, uint32_t a3, uint64_t db, uint32_t accum) {
  asm volatile("{\n.reg .pred p;\nsetp.ne.b32 p, %22, 0;\nwgmma.mma_async.sync.aligned.m64n32k16.f32.bf16.bf16 "
    "{%0, %1, %2, %3, %4, %5, %6, %7, %8, %9, %10, %11, %12, %13, %14, %15}"
    ", {%16, %17, %18, %19}, %20, p, 1, 1, %21;\n}\n"
    :
      "+f"(d[OFF + 0]), "+f"(d[OFF + 1]), "+f"(d[OFF + 2]), "+f"(d[OFF + 3]), "+f"(d[OFF + 4]), "+f"(d[OFF + 5]), "+f"(d[OFF + 6]), "+f"(d[OFF + 7]), "+f"(d[OFF + 8]), "+f"(d[OFF + 9]), "+f"(d[OFF + 10]), "+f"(d[OFF + 11]), "+f"(d[OFF + 12]), "+f"(d[OFF + 13]), "+f"(d[OFF + 14]), "+f"(d[OFF + 15])
    : "r"(a0), "r"(a1), "r"(a2), "r"(a3), "l"(db), "n"(TB), "r"(accum));
}

template <int J0 = 0, int J1 = 8>
__device__ __forceinline__ void stage_tile(const float (&d)[64], uint32_t stg, int w, int lane, uint32_t sgn) {
  const int r = 16 * w + (lane & 7) + ((lane >> 3) & 1) * 8;
  const uint32_t rowa = stg + r * 128;
  const int hi = lane >> 4, sw = r & 7;
#pragma unroll
  for (int jj = J0; jj < J1; jj++) {
    const int chunk = 2 * (jj & 3) + hi;
    const uint32_t addr = rowa + (jj >> 2) * 8192 + ((chunk ^ sw) << 4);
    stsm4(addr, pack2(d[8 * jj], d[8 * jj + 1]) ^ sgn, pack2(d[8 * jj + 2], d[8 * jj + 3]) ^ sgn,
          pack2(d[8 * jj + 4], d[8 * jj + 5]) ^ sgn, pack2(d[8 * jj + 6], d[8 * jj + 7]) ^ sgn);
  }
}

__device__ __forceinline__ void rowmax(const float (&s)[32], float& x0, float& x1) {
  float a0 = fmaxf(s[0], s[1]), a1 = fmaxf(s[2], s[3]), b0 = fmaxf(s[4], s[5]), b1 = fmaxf(s[6], s[7]);
#pragma unroll
  for (int i = 8; i < 32; i += 8) {
    a0 = fmaxf(a0, fmaxf(s[i], s[i + 1])); a1 = fmaxf(a1, fmaxf(s[i + 2], s[i + 3]));
    b0 = fmaxf(b0, fmaxf(s[i + 4], s[i + 5])); b1 = fmaxf(b1, fmaxf(s[i + 6], s[i + 7]));
  }
  x0 = fmaxf(a0, b0); x1 = fmaxf(a1, b1);
  x0 = fmaxf(x0, __shfl_xor_sync(~0u, x0, 1)); x1 = fmaxf(x1, __shfl_xor_sync(~0u, x1, 1));
  x0 = fmaxf(x0, __shfl_xor_sync(~0u, x0, 2)); x1 = fmaxf(x1, __shfl_xor_sync(~0u, x1, 2));
}
__device__ __forceinline__ void exps(float (&s)[32], float mc0, float mc1) {
#pragma unroll
  for (int i = 0; i < 32; i++) s[i] = ex2(fmaf(s[i], SC, (i & 2) ? mc1 : mc0));
}
#define PK(lo, hi, row) pack2(lo, hi)
#define XO_PARAM
#define XO_ARG
__device__ __forceinline__ void packp(const float (&s)[32], uint32_t (&p)[16]) {
#pragma unroll
  for (int i = 0; i < 16; i++) p[i] = pack2(s[2 * i], s[2 * i + 1]);
}
template <int W, int HALF>
__device__ __forceinline__ void xy_exp(const float (&s)[32], uint32_t (&p)[16], float mc0, float mc1, float vbl, bool c0, bool c1,
                                       uint32_t M XO_PARAM) {
  const float ml0 = mc0 + vbl, ml1 = mc1 + vbl;
#pragma unroll
  for (int c = 0; c < 2; c++) {
    const int j = 2 * HALF + c, L = 8 * c, H = 16 + 8 * c;
    if (j != W) {
      const int of = j > W ? L : H;
      const float m0 = j > W ? ml0 : mc0, m1 = j > W ? ml1 : mc1;
#pragma unroll
      for (int r = 0; r < 4; r++) {
        const float m = (r & 1) ? m1 : m0;
        const uint32_t v = PK(ex2(fmaf(s[of + 2 * r], SC, m)), ex2(fmaf(s[of + 2 * r + 1], SC, m)), r & 1);
        p[4 * c + r] = j > W ? v : 0u;
        p[8 + 4 * c + r] = j > W ? 0u : v;
      }
    } else {
      const uint32_t v0 = PK(ex2(c0 ? fmaf(s[L + 0], SC, ml0) : fmaf(s[H + 0], SC, mc0)),
                             ex2(c1 ? fmaf(s[L + 1], SC, ml0) : fmaf(s[H + 1], SC, mc0)), 0);
      const uint32_t v3 = PK(ex2(c0 ? fmaf(s[L + 6], SC, ml1) : fmaf(s[H + 6], SC, mc1)),
                             ex2(c1 ? fmaf(s[L + 7], SC, ml1) : fmaf(s[H + 7], SC, mc1)), 1);
      p[4 * c + 0] = v0 & M;  p[8 + 4 * c + 0] = v0 & ~M;
      p[4 * c + 1] = 0;       p[8 + 4 * c + 1] = PK(ex2(fmaf(s[H + 2], SC, mc1)), ex2(fmaf(s[H + 3], SC, mc1)), 1);
      p[4 * c + 2] = PK(ex2(fmaf(s[L + 4], SC, ml0)), ex2(fmaf(s[L + 5], SC, ml0)), 0);  p[8 + 4 * c + 2] = 0;
      p[4 * c + 3] = v3 & M;  p[8 + 4 * c + 3] = v3 & ~M;
    }
  }
}
template <int W> __device__ __forceinline__ void x_exp(const float (&s)[32], uint32_t (&p)[16], float mc0, float mc1, float vbl, bool c0,
                                                       bool c1, uint32_t M XO_PARAM) { xy_exp<W, 0>(s, p, mc0, mc1, vbl, c0, c1, M XO_ARG); }
template <int W> __device__ __forceinline__ void y_exp(const float (&s)[32], uint32_t (&p)[16], float mc0, float mc1, float vbl, bool c0,
                                                       bool c1, uint32_t M XO_PARAM) { xy_exp<W, 1>(s, p, mc0, mc1, vbl, c0, c1, M XO_ARG); }
#define WARP_SWITCH(F, ...)                                                  \
  do {                                                                        \
    if (warp & 2) { if (warp & 1) F<3>(__VA_ARGS__); else F<2>(__VA_ARGS__); } \
    else { if (warp & 1) F<1>(__VA_ARGS__); else F<0>(__VA_ARGS__); }          \
  } while (0)
#define PV_MMA wgmma_rs_n24
__device__ __forceinline__ void issue_pv_sum(float (&o)[12], const uint32_t (&p)[16], uint32_t vlo) {
#pragma unroll
  for (int c = 0; c < 4; c++)
    wgmma_rs_n24<1, 1>(o, p[c * 4 + 0], p[c * 4 + 1], p[c * 4 + 2], p[c * 4 + 3], desc32(vlo - (uint32_t)c * (32u * 65535u)));
}
template <int FIRST>
__device__ __forceinline__ void issue_pv(float (&o)[12], const uint32_t (&p)[16], uint32_t vlo) {
#pragma unroll
  for (int c = 0; c < 4; c++) {
    const uint64_t d = desc32(vlo - (uint32_t)c * (32u * 65535u));
    if (FIRST && c == 0) PV_MMA<1, 0>(o, p[0], p[1], p[2], p[3], d);
    else PV_MMA<1, 1>(o, p[c * 4 + 0], p[c * 4 + 1], p[c * 4 + 2], p[c * 4 + 3], d);
  }
}

__device__ __forceinline__ void issue_pv2(float (&o)[12], const uint32_t (&p)[16], uint32_t vlo, uint32_t vhi) {
#pragma unroll
  for (int c = 0; c < 4; c++) {
    const uint64_t d = desc32((c < 2 ? vlo : vhi) - (uint32_t)(c & 1) * (32u * 65535u));
    PV_MMA<1, 1>(o, p[c * 4 + 0], p[c * 4 + 1], p[c * 4 + 2], p[c * 4 + 3], d);
  }
}

}

#define QSTEP 1
#define GEMM_KBLOCK(first, RELEASE)                                                                     \
  do {                                                                                                   \
    const uint32_t sta_ = sd + (OFF_RING >> 4) + p * 2048;                                               \
    const uint32_t lo_ = sta_ | 0x10000u, lob_ = (sta_ + 1024) | (512u << 16);                           \
    wgmma_fence();                                                                                       \
    _Pragma("unroll") for (int kk = 0; kk < 4; kk++) {                                                   \
      const uint64_t db_ = desc128(lob_ + kk * 128);                                                     \
      const uint32_t ac_ = kk > 0 ? 1u : (uint32_t)!(first);                                             \
      wgmma_ss_n128<1>(acc0, desc128(lo_ + kk * 2), db_, ac_);                                           \
      wgmma_ss_n128<1>(acc1, desc128(lo_ + 512 + kk * 2), db_, ac_);                                     \
      if ((kk & (QSTEP - 1)) == QSTEP - 1) {                                                             \
        wgmma_commit();                                                                                  \
        wgmma_wait<1>();                                                                                 \
        if (kk == QSTEP - 1 && (RELEASE) && rel_pred) mbar_arrive_cluster(bar + B_EMPTYA + 8 * pprev, rel_cta); \
      }                                                                                                  \
    }                                                                                                    \
  } while (0)

#define APF 3
#define KQ_STEP 2
#define KQ_NEXT(m, kq)                                                                                   \
  do {                                                                                                    \
    kq = (kq + ((m) >= 1 && (m) < 31 ? 2 : 1)) & 31;                                                      \
    if ((m) == 1) kq = (2 * rb + 2) & 31;                                                                 \
    if ((m) == (isY ? (NY + 1) / 2 : 16)) kq = (2 * rb + 3) & 31;                                         \
    if ((m) == 31) kq = (2 * rb + NY) & 31;                                                               \
  } while (0)
__host__ __device__ constexpr uint32_t uses_mask(int nk) {
  uint32_t m = 0x18;
  for (int i = 0; i < nk; i++) m ^= 1u << ((3 + i) % 5);
  return m;
}

__global__ void __cluster_dims__(2, 1, 1) __launch_bounds__(512, 1)
concat_heads__spectral_fnet__sliding_block__prompt_kernel(const __grid_constant__ Params P) {
  extern __shared__ uint8_t smem_raw[];
  const uint32_t sb = (smem_u32(smem_raw) + 1023) & ~1023u;
  const uint32_t bar = sb + OFF_BAR;
  const uint32_t sd = (sb & 0x3FFFFu) >> 4;
  const int wid = __shfl_sync(~0u, threadIdx.x >> 5, 0);
  const int wg = wid >> 2, warp = wid & 3;
  const int lane = threadIdx.x & 31;
  const int tid = threadIdx.x & 127;
  const int rank = blockIdx.x & 1;
  const int cl = blockIdx.x >> 1;
  const int rb = cl >> 2;
  const int q4 = cl & 3;
  const int isY = q4 & 1;
  const int cp = q4 >> 1;
  const int eb2 = 2 * cp + rank;
  const int nb1 = 2 * q4 + rank;
  const int tile = rb * 4 + eb2;

  if (wid < 2) {
    const int i = wid * 32 + lane;
    lsu_prefetch(P.p_xb + (size_t)(rb * 128 + (q4 * 2 + rank) * 16 + (i >> 2)) * 1024 + (i & 3) * 128);
  } else if (wid < 5) {
    if (lane < 16) lsu_prefetch(P.p_wq + (size_t)(rb * 16 + lane) * 3072 + (wid - 2) * 1024 + nb1 * 128);
  }
  if (elect_one()) {
    const uint32_t c2 = (uint32_t)((wid < 8 ? BAR_CNT_LO : BAR_CNT_HI) >> ((wid & 7) * 8));
    mbar_init(bar + wid * 16, c2 & 15);
    mbar_init(bar + wid * 16 + 8, (c2 >> 4) & 15);
    if (wid >= 9) mbar_init(bar + B_ORDY + (15 - wid) * 8, wid == 11 ? 4 : 1);
    asm volatile("fence.mbarrier_init.release.cluster;" ::: "memory");
    if (wid < 11) map_prefetch(&P.xb + wid);
  }
  if (wg >= 2) asm volatile("st.shared.u32 [%0], %1;" ::"r"(sb + OFF_ONES + tid * 4), "r"(0x3f803f80u) : "memory");
  cluster_arrive();
  cluster_wait();
  const int arow = rb * 128 + rank * 64;
#define B1_OPS(e)                                                                                          \
      tma_load_mc(xa_, &P.xb, (e) * 64, arow, fb_);                                                        \
      tma_load(wb_, &P.wqkv, nb1 * 64, (e) * 64, fb_);                                                     \
      tma_load(wb_ + 8192, &P.wqkv, 512 + nb1 * 64, (e) * 64, fb_);                                        \
      tma_load(wb_ + 16384, &P.wqkv, 1024 + nb1 * 64, (e) * 64, fb_);
#define B1_LOAD(e)                                                                                        \
  do {                                                                                                     \
    const uint32_t j_ = (e) & 3;                                                                           \
    const uint32_t wb_ = sb + OFF_RING + (j_ < 2 ? j_ * 40960 : 98304 + (j_ - 2) * 32768);                 \
    const uint32_t xa_ = rank == 0 ? wb_ + 24576 : (j_ < 2 ? wb_ + 32768 : sb + OFF_KV + 32768 + (j_ - 2) * 8192); \
    const uint32_t fb_ = bar + B_FULLB + 8 * j_;                                                           \
    if (elect_one()) {                                                                                     \
      mbar_expect_tx(fb_, 40960);                                                                          \
      B1_OPS(e)                                                                                            \
    }                                                                                                      \
  } while (0)
  if (is_eq(wid, 0)) {
    if (lane == 0) asm volatile("st.shared.v2.u32 [%0], {%1, %1};" ::"r"(bar + B_MSK), "r"(0) : "memory");
    __syncwarp();
#pragma unroll
    for (int e = 0; e < 4; e++) { B1_LOAD(e); }
  }

  if (is_eq(wg, 0)) {
    reg_dealloc<24>();
    unsigned ep = 0;
    if (is_eq(warp, 0)) {
      uint32_t useA = 0;
      uint32_t p = 0;
#pragma unroll 1
      for (int e = 4; e < 8; e++) {
        mbar_wait(bar + B_EMPTYB + 8 * (e & 3), 0);
        __syncwarp();
        B1_LOAD(e);
      }
      asm volatile("ld.relaxed.gpu.global.u32 %0, [%1];" : "=r"(ep) : "l"(P.epoch + blockIdx.x * 32));
      {
        const CUtensorMap* mw = isY ? &P.wi : &P.wr;
#pragma unroll 1
        for (int n = 0; n < 8; n++) {
          if (n < 5) mbar_wait(bar + B_EMPTYB + 8 * (n == 0 ? 0 : (n <= 2 ? 1 : n - 1)), 1);
          else mbar_wait(bar + B_EMPTYA + 8 * p, 0);
          __syncwarp();
          const uint32_t st = sb + OFF_RING + p * 32768, fb = bar + B_FULLA + 8 * p;
          if (elect_one()) {
            mbar_expect_tx(fb, 32768);
            tma_load_mc(st + rank * 8192, &P.xa, n * 64, arow, fb);
            tma_load(st + 16384, mw, n * 64, eb2 * 128, fb);
          }
          useA ^= 1u << p;
          p = (p == 4) ? 0 : p + 1;
        }
      }
      {
        const CUtensorMap* mc = isY ? &P.ci : &P.cr;
        uint32_t kq = 2 * rb, par = 0;
        p = 3;
#define A2_LOAD_A(m, map)                                                                                 \
          mbar_wait(bar + B_EMPTYA + 8 * p, par);                                                          \
          if (elect_one()) {                                                                               \
            const uint32_t fb = bar + B_FULLA + 8 * p;                                                     \
            mbar_expect_tx(fb, (m) < 2 ? 16384 : 32768);                                                   \
            tma_load_mc(sb + OFF_RING + p * 32768 + rank * 8192, map, kq * 64, arow, fb);                  \
          }                                                                                                \
          if (p == 4) { p = 0; par ^= 1; } else p++;
        const int nk1 = isY ? NY : 32;
#pragma unroll 1
        for (int m = 0; m < nk1; m++) {
          A2_LOAD_A(m, mc);
          KQ_NEXT(m, kq);
          if (m == APF + 2) {
            uint32_t k2 = (2 * rb + 2) & 31;
#pragma unroll 1
            for (int j = 0; j < 3; j++) {
              smem_mask_wait(bar + B_MSK + (k2 & 1) * 4, 1u << (isY * 16 + (k2 >> 1)));
              if (elect_one())
                bulk_load(sb + OFF_RING + j * 32768 + 16384, P.ab + (size_t)((isY * 32 + k2) * 4 + eb2) * 16384, 16384,
                          bar + B_FULLA + 8 * j);
              k2 = (k2 + KQ_STEP) & 31;
            }
            if (lane == 0) mbar_arrive(bar + B_M4I);
          }
        }
        if (!isY) {
#pragma unroll 1
          for (int m = 32; m < NX; m++) {
            A2_LOAD_A(m, &P.ci);
            kq = (kq + 1) & 31;
          }
        }
        useA = isY ? uses_mask(NY) : uses_mask(NX);
      }
      if (isY) {
        p = (NY + 3) % 5;
#pragma unroll 1
        for (int i = 0; i < 8; i++) {
          mbar_wait(bar + B_EMPTYA + 8 * p, (useA >> p & 1) ^ 1);
          __syncwarp();
          const uint32_t st = sb + OFF_RING + p * 32768, fb = bar + B_FULLA + 8 * p;
          if (elect_one()) {
            mbar_expect_tx(fb, 32768);
            tma_load4(st + 16384, &P.wo4, eb2 * 128, 0, i >> 1, (i & 1) * 4, fb);
            tma_load4(st + 24576, &P.wo4, eb2 * 128 + 64, 0, i >> 1, (i & 1) * 4, fb);
          }
          if ((i & 1) == 0) {
            mbar_wait(bar + B_ORDY + (i >> 1) * 8, 0);
            __syncwarp();
          }
          if (elect_one()) tma_load_mc(st + rank * 8192, &P.o, i * 64, arow, fb);
          if (i == PSD && lane == 0) mbar_arrive(bar + B_ARD2);
          if (i == PSD2 && lane == 0) mbar_arrive(bar + B_ARD);
          useA ^= 1u << p;
          p = (p == 4) ? 0 : p + 1;
        }
      } else {
        const uint32_t stg = sb + OFF_KV;
        const int row = rb * 128, col = eb2 * 128;
        flag_wait(P.flags + (F_P + tile) * 32, ep + 1);
        mbar_wait(bar + B_PST, 0);
        __syncwarp();
        if (lane == 0) { tma_red_add(&P.out, stg, col, row); tma_red_add(&P.out, stg + 8192, col + 64, row); bulk_commit(); }
        mbar_wait(bar + B_PST + 8, 0);
        __syncwarp();
        if (lane == 0) {
          tma_red_add(&P.out, stg + 16384, col, row + 64); tma_red_add(&P.out, stg + 24576, col + 64, row + 64);
          bulk_commit();
          bulk_wait_read<0>();
        }
      }
    } else if (is_eq(warp, 1)) {
      const int lb0 = rb >= 2 ? 0 : 4 - 2 * rb;
      asm volatile("ld.relaxed.gpu.global.u32 %0, [%1];" : "=r"(ep) : "l"(P.epoch + blockIdx.x * 32));
      mbar_wait(bar + B_B1END, 0);
      __syncwarp();
      {
        int r = rb - (lane % 3);
        r = r < 0 ? 0 : r;
        flag_wait(P.flags + (F_KV + r * 8 + nb1) * 32, (ep + 1) * 2);
      }
      const unsigned* fl2 = P.flags + (F_KV + max(rb - (lane % 3), 0) * 8 + nb1) * 32 + 1;
#pragma unroll 1
      for (int h = 0; h < 4; h++) {
        const int b = h & 1;
        if (h >= 2) { mbar_wait(bar + B_KVEMPTY + 8 * b, 0); __syncwarp(); }
        if (h == 1) flag_wait(fl2, (ep + 1) * 2);
        const uint32_t bytes = (6 - lb0) * 4096;
        if (elect_one()) {
          mbar_expect_tx(bar + B_KVFULL + 8 * b, bytes);
          bulk_load(sb + OFF_KV + b * 24576 + lb0 * 4096, P.kv + (size_t)((nb1 * 4 + h) * 32 + 2 * rb - 4 + lb0) * 4096, bytes,
                    bar + B_KVFULL + 8 * b);
        }
      }
      if (isY) {
#pragma unroll 1
        for (int h = 0; h < 4; h++) {
          flag_wait(P.flags + (F_O + rb * 4 + h) * 32, (ep + 1) * 8);
          if (lane == 0) mbar_arrive(bar + B_ORDY + h * 8);
        }
      }
    } else if (is_eq(warp, 2)) {
      asm volatile("ld.relaxed.gpu.global.u32 %0, [%1];" : "=r"(ep) : "l"(P.epoch + blockIdx.x * 32));
      mbar_wait(bar + B_B1END, 0);
      __syncwarp();
      flag_watch(P.flags + (F_A + eb2 * 32) * 32 + lane, 2 * ep + 1, isY ? 0xFFFF0000u : 0xFFFFFFFFu, bar + B_MSK, lane == 0);
#pragma unroll 1
      for (int h = 0; h < 4; h++) {
        mbar_wait(bar + B_OST + 8 * h, 0);
        __syncwarp();
        if (lane == 0) {
          tma_store(&P.o16, sb + OFF_QS + h * 4096, h * 128 + nb1 * 16, rb * 128);
          bulk_commit();
          bulk_wait_all();
          flag_add(P.flags + (F_O + rb * 4 + h) * 32);
        }
      }
    } else {
      uint8_t* gt = P.ab + (size_t)((isY * 32 + 2 * rb) * 4 + eb2) * 16384;
      unsigned* f = P.flags + (F_A + eb2 * 32) * 32 + (isY * 16 + rb);
      const uint32_t stg = sb + OFF_RING + 3 * 32768 + 16384;
      mbar_wait(bar + B_A1I, 0);
      __syncwarp();
      if (lane == 0) bulk_store(gt, stg, 8192);
      mbar_wait(bar + B_AST, 0);
      __syncwarp();
      if (lane == 0) { bulk_store(gt + 8192, stg + 8192, 8192); bulk_commit(); }
      if (lane == 0) { bulk_wait_all(); flag_add(f); }
      __syncwarp();
      mbar_wait(bar + B_AST + 8, 0);
      mbar_wait(bar + B_M4I, 0);
      __syncwarp();
      if (lane == 0) { bulk_store(gt + 65536, stg + 32768, 16384); bulk_commit(); }
      __syncwarp();
      lsu_prefetch(P.p_wo + blockIdx.x * 4096 + lane * 128);
      {
        const int nk = isY ? NY : NX;
        uint32_t kq = (2 * rb + 2 + 3 * KQ_STEP) & 31, par = 1, p = 3, half = isY;
#pragma unroll 1
        for (int m = 5; m < nk; m++) {
          if (m == 6) {
            if (lane == 0) { bulk_wait_all(); flag_add(f); }
            __syncwarp();
          }
          smem_mask_wait(bar + B_MSK + (kq & 1) * 4, 1u << (half * 16 + (kq >> 1)));
          mbar_wait(bar + B_EMPTYA + 8 * p, par);
          if (elect_one())
            bulk_load(sb + OFF_RING + p * 32768 + 16384, P.ab + (size_t)((half * 32 + kq) * 4 + eb2) * 16384, 16384,
                      bar + B_FULLA + 8 * p);
          if (p == 4) { p = 0; par ^= 1; } else p++;
          KQ_NEXT(m, kq);
          if (m == 31) half = 1;
        }
      }
      if (isY) {
        mbar_wait(bar + B_PST, 0);
        mbar_wait(bar + B_ARD2, 0);
        __syncwarp();
        if (lane == 0) {
          tma_store(&P.out, sb + OFF_KV, eb2 * 128, rb * 128);
          tma_store(&P.out, sb + OFF_KV + 8192, eb2 * 128 + 64, rb * 128);
          bulk_commit();
        }
        mbar_wait(bar + B_PST + 8, 0);
        mbar_wait(bar + B_ARD, 0);
        __syncwarp();
        if (lane == 0) {
          tma_store(&P.out, sb + OFF_KV + 16384, eb2 * 128, rb * 128 + 64);
          tma_store(&P.out, sb + OFF_KV + 24576, eb2 * 128 + 64, rb * 128 + 64);
          bulk_commit();
          bulk_wait_all();
          flag_add(P.flags + (F_P + tile) * 32);
        }
      }
    }
    __syncwarp();
    cluster_arrive();
    cluster_wait();
    if (threadIdx.x == 0) P.epoch[blockIdx.x * 32] = ep + 1;
  } else if (is_eq(wg, 1)) {
    reg_alloc<168>();
    float acc0[64], acc1[64];
    uint32_t ph = 0, p = 0;
    const uint32_t rel_pred = (lane == 0);
    const uint32_t rel_cta = warp & 1;
    uint32_t pprev = 0;
    mbar_wait(bar + B_B1END, 0);
#pragma unroll 1
    for (int n = 0; n < 7; n++) {
      mbar_wait(bar + B_FULLA + 8 * p, (ph >> p) & 1);
      ph ^= 1u << p;
      const uint32_t lo = (sd + (OFF_RING >> 4) + p * 2048) | 0x10000u;
      wgmma_fence();
#pragma unroll
      for (int kk = 0; kk < 4; kk++) {
        const uint64_t db = desc128(lo + 1024 + kk * 2);
        const uint32_t ac = kk > 0 ? 1u : (uint32_t)(n > 0);
        wgmma_ss_n128<0>(acc0, desc128(lo + kk * 2), db, ac);
        wgmma_ss_n128<0>(acc1, desc128(lo + 512 + kk * 2), db, ac);
      }
      wgmma_commit();
      if (n > 0) {
        wgmma_wait<1>();
        if (rel_pred) mbar_arrive_cluster(bar + B_EMPTYA + 8 * pprev, rel_cta);
      }
      pprev = p;
      p = (p == 4) ? 0 : p + 1;
    }
    {
      mbar_wait(bar + B_FULLA + 8 * 2, (ph >> 2) & 1);
      ph ^= 1u << 2;
      const uint32_t lo = (sd + (OFF_RING >> 4) + 2 * 2048) | 0x10000u;
      wgmma_fence();
#pragma unroll
      for (int kk = 0; kk < 4; kk++) wgmma_ss_n128<0>(acc0, desc128(lo + kk * 2), desc128(lo + 1024 + kk * 2), 1u);
      wgmma_commit();
#pragma unroll
      for (int kk = 0; kk < 4; kk++) wgmma_ss_n128<0>(acc1, desc128(lo + 512 + kk * 2), desc128(lo + 1024 + kk * 2), 1u);
      wgmma_commit();
      wgmma_wait<2>();
      if (rel_pred) mbar_arrive_cluster(bar + B_EMPTYA + 8 * 1, rel_cta);
      const uint32_t sgn = isY ? 0x80008000u : 0u;
      const uint32_t stg = sb + OFF_RING + 3 * 32768 + 16384;
      named_bar<1>();
      wgmma_wait<1>();
      fregs(acc0);
      stage_tile<0, 4>(acc0, stg, warp, lane, sgn);
      fence_async_smem();
      __syncwarp();
      if (lane == 0) mbar_arrive(bar + B_A1I);
      stage_tile<4, 8>(acc0, stg, warp, lane, sgn);
      fence_async_smem();
      __syncwarp();
      if (lane == 0) mbar_arrive(bar + B_AST);
      wgmma_wait<0>();
      fregs(acc1);
      if (rel_pred) mbar_arrive_cluster(bar + B_EMPTYA + 8 * 2, rel_cta);
      stage_tile(acc1, stg + 32768, warp, lane, sgn);
      fence_async_smem();
      __syncwarp();
      if (lane == 0) mbar_arrive(bar + B_AST + 8);
      named_bar<1>();
      p = 3;
    }
    const int nk = isY ? NY : NX;
#define GEMM_KLAST()                                                                                     \
    do {                                                                                                 \
      const uint32_t sta_ = sd + (OFF_RING >> 4) + p * 2048;                                             \
      const uint32_t lo_ = sta_ | 0x10000u, lob_ = (sta_ + 1024) | (512u << 16);                         \
      wgmma_fence();                                                                                     \
      _Pragma("unroll") for (int kk = 0; kk < 4; kk++)                                                   \
        wgmma_ss_n128<1>(acc0, desc128(lo_ + kk * 2), desc128(lob_ + kk * 128), 1u);                     \
      wgmma_commit();                                                                                    \
      _Pragma("unroll") for (int kk = 0; kk < 4; kk++)                                                   \
        wgmma_ss_n128<1>(acc1, desc128(lo_ + 512 + kk * 2), desc128(lob_ + kk * 128), 1u);               \
      wgmma_commit();                                                                                    \
      wgmma_wait<2>();                                                                                   \
    } while (0)
#pragma unroll 1
    for (int m = 0; m < nk - 1; m++) {
      mbar_wait(bar + B_FULLA + 8 * p, (ph >> p) & 1);
      ph ^= 1u << p;
      GEMM_KBLOCK(m == 0, m > 0);
      pprev = p;
      p = (p == 4) ? 0 : p + 1;
    }
    {
      mbar_wait(bar + B_FULLA + 8 * p, (ph >> p) & 1);
      ph ^= 1u << p;
      GEMM_KLAST();
      if (rel_pred) mbar_arrive_cluster(bar + B_EMPTYA + 8 * pprev, rel_cta);
#pragma unroll 1
      for (int h = 0; h < 4; h++) mbar_wait(bar + B_OST + 8 * h, 0);
      const uint32_t stg = sb + OFF_KV;
      wgmma_wait<1>();
      fregs(acc0);
      stage_tile(acc0, stg, warp, lane, 0);
      fence_async_smem();
      __syncwarp();
      if (lane == 0) mbar_arrive(bar + B_PST);
      pprev = p;
      p = (p == 4) ? 0 : p + 1;
      if (!isY) {
        wgmma_wait<0>();
        fregs(acc1);
        if (rel_pred) mbar_arrive_cluster(bar + B_EMPTYA + 8 * pprev, rel_cta);
        stage_tile(acc1, stg + 16384, warp, lane, 0);
        fence_async_smem();
        __syncwarp();
        if (lane == 0) mbar_arrive(bar + B_PST + 8);
      } else {
      {
        mbar_wait(bar + B_FULLA + 8 * p, (ph >> p) & 1);
        ph ^= 1u << p;
        const uint32_t sta_ = sd + (OFF_RING >> 4) + p * 2048;
        const uint32_t lo_ = sta_ | 0x10000u, lob_ = (sta_ + 1024) | (512u << 16);
        wgmma_fence();
#pragma unroll
        for (int kk = 0; kk < 4; kk++) wgmma_ss_n128<1>(acc0, desc128(lo_ + kk * 2), desc128(lob_ + kk * 128), kk > 0 ? 1u : 0u);
        wgmma_commit();
        wgmma_wait<1>();
        fregs(acc1);
        if (rel_pred) mbar_arrive_cluster(bar + B_EMPTYA + 8 * pprev, rel_cta);
        stage_tile(acc1, stg + 16384, warp, lane, 0);
        fence_async_smem();
        __syncwarp();
        if (lane == 0) mbar_arrive(bar + B_PST + 8);
        wgmma_fence();
#pragma unroll
        for (int kk = 0; kk < 4; kk++) wgmma_ss_n128<1>(acc1, desc128(lo_ + 512 + kk * 2), desc128(lob_ + kk * 128), kk > 0 ? 1u : 0u);
        wgmma_commit();
        pprev = p;
        p = (p == 4) ? 0 : p + 1;
      }
#pragma unroll 1
      for (int i = 1; i < 7; i++) {
        mbar_wait(bar + B_FULLA + 8 * p, (ph >> p) & 1);
        ph ^= 1u << p;
        GEMM_KBLOCK(false, i < 4);
        pprev = p;
        p = (p == 4) ? 0 : p + 1;
      }
      mbar_wait(bar + B_FULLA + 8 * p, (ph >> p) & 1);
      GEMM_KLAST();
      const uint32_t stg = sb + OFF_RING + ((NY + 3 + 3) % 5) * 32768;
      const int row = rb * 128, col = 512 + eb2 * 128;
      named_bar<1>();
      wgmma_wait<1>();
      fregs(acc0);
      stage_tile(acc0, stg, warp, lane, 0);
      fence_async_smem();
      named_bar<1>();
      if (tid == 0) { tma_store(&P.out, stg, col, row); tma_store(&P.out, stg + 8192, col + 64, row); bulk_commit(); }
      wgmma_wait<0>();
      fregs(acc1);
      stage_tile(acc1, stg + 16384, warp, lane, 0);
      fence_async_smem();
      named_bar<1>();
      if (tid == 0) {
        tma_store(&P.out, stg + 16384, col, row + 64);
        tma_store(&P.out, stg + 24576, col + 64, row + 64);
        bulk_commit();
        bulk_wait_read<0>();
      }
    }
    }
    __syncwarp();
    cluster_arrive();
    cluster_wait();
  } else {
    reg_alloc<160>();
    const int a = wg - 2;
    const int g = lane >> 2, t = lane & 3;
    const uint32_t qs = sb + OFF_QS + a * 2048 + tid * 16;
    {
      const uint32_t rel_pred = (lane == 0) && (warp < 2);
      const uint32_t rel_cta = warp & 1;
      float acc[96];
#pragma unroll 1
      for (int e = 0; e < 8; e++) {
        const uint32_t j = e & 3;
        mbar_wait(bar + B_FULLB + 8 * j, (e >> 2) & 1);
        const uint32_t wb = (j < 2 ? j * 40960 : 98304 + (j - 2) * 32768);
        const uint32_t xa = a == 0 ? wb + 24576 : (j < 2 ? wb + 32768 : OFF_KV + 32768 + (j - 2) * 8192);
        const uint32_t lo = (sd + (xa >> 4)) | 0x10000u, lob = (sd + (wb >> 4)) | (512u << 16);
        wgmma_fence();
#pragma unroll
        for (int kk = 0; kk < 4; kk++) wgmma_ss_n192<1>(acc, desc128(lo + kk * 2), desc128(lob + kk * 128), kk > 0 ? 1u : (uint32_t)(e > 0));
        wgmma_commit();
        if (e == 7 && tid == 0) mbar_arrive(bar + B_B1END);
        if (e > 0) {
          wgmma_wait<1>();
          if (rel_pred) mbar_arrive_cluster(bar + B_EMPTYB + 8 * ((e - 1) & 3), rel_cta);
        }
      }
      wgmma_wait<0>();
      fregs(acc);
      if (rel_pred) mbar_arrive_cluster(bar + B_EMPTYB + 8 * 3, rel_cta);
      if (a == 1) asm volatile("bar.arrive 7, 256;" ::: "memory");
      const uint32_t stg = sb + OFF_KV;
      const uint32_t s1 = a == 0 ? 24576 : 32768, s3 = a == 0 ? 45056 : 40960;
      const uint32_t s0 = a * 4096;
      uint8_t* gkv = P.kv + (size_t)(nb1 * 4 * 32 + 2 * rb + a) * 4096;
      unsigned* fkv = P.flags + (F_KV + rb * 8 + nb1) * 32;
      {
        const int r = 16 * warp + (lane & 7) + ((lane >> 3) & 1) * 8;
        const uint32_t ad = stg + r * 32 + (((lane >> 4) ^ ((r >> 2) & 1)) << 4);
#pragma unroll
        for (int h = 0; h < 4; h++) {
          const uint32_t o = h == 0 ? s0 : (h == 3 ? s3 : s1 + (h - 1) * 4096);
          if (h == 3 && a == 0) asm volatile("bar.sync 7, 256;" ::: "memory");
          stsm4(ad + o, pack2(acc[32 + 8 * h], acc[32 + 8 * h + 1]), pack2(acc[32 + 8 * h + 2], acc[32 + 8 * h + 3]),
                pack2(acc[32 + 8 * h + 4], acc[32 + 8 * h + 5]), pack2(acc[32 + 8 * h + 6], acc[32 + 8 * h + 7]));
          stsm4(ad + o + 2048, pack2(acc[64 + 8 * h], acc[64 + 8 * h + 1]), pack2(acc[64 + 8 * h + 2], acc[64 + 8 * h + 3]),
                pack2(acc[64 + 8 * h + 4], acc[64 + 8 * h + 5]), pack2(acc[64 + 8 * h + 6], acc[64 + 8 * h + 7]));
          if (h == 0) {
            fence_async_smem();
            named_bar23(a);
            if (tid == 0) { bulk_store(gkv, stg + s0, 4096); bulk_commit(); }
          }
        }
      }
      fence_async_smem();
      named_bar23(a);
      if (tid == 0) {
#pragma unroll
        for (int h = 1; h < 4; h++) bulk_store(gkv + h * 32 * 4096, stg + (h == 3 ? s3 : s1 + (h - 1) * 4096), 4096);
        bulk_commit();
      }
#pragma unroll
      for (int h = 0; h < 4; h++) {
        asm volatile("st.shared.v4.u32 [%0], {%1, %2, %3, %4};" ::"r"(qs + h * 4096), "r"(pack2(acc[8 * h], acc[8 * h + 1])),
                     "r"(pack2(acc[8 * h + 2], acc[8 * h + 3])), "r"(pack2(acc[8 * h + 4], acc[8 * h + 5])),
                     "r"(pack2(acc[8 * h + 6], acc[8 * h + 7])) : "memory");
      }
      if (tid == 0) {
        asm volatile("cp.async.bulk.wait_group 1;" ::: "memory");
        flag_add(fkv);
        bulk_wait_all();
        flag_add(fkv + 1);
      }
      __syncwarp();
    }
    {
      const int lb0 = rb >= 2 ? 0 : 4 - 2 * rb;
      const uint32_t onesw = (sd + (OFF_ONES >> 4)) << 16;
      const int lhi = a + 4;
      const bool lov = a >= lb0;
      const int llo = lov ? a : lhi;
      const int l1 = a + 1 >= lb0 ? a + 1 : lhi, l2 = a + 2 >= lb0 ? a + 2 : lhi, l3 = a + 3 >= lb0 ? a + 3 : lhi;
      const float vbl = lov ? 0.f : -INFINITY;
      const float vb1 = a + 1 >= lb0 ? 0.f : -INFINITY, vb2 = a + 2 >= lb0 ? 0.f : -INFINITY, vb3 = a + 3 >= lb0 ? 0.f : -INFINITY;
      const int u = 2 * t - g;
      const bool c0 = u > 0, c1 = u + 1 > 0;
      const uint32_t Mx = u > 0 ? 0xFFFFFFFFu : (u == 0 ? 0xFFFF0000u : 0u);
      const uint32_t ost = sb + OFF_QS + a * 2048 + warp * 512 + ((lane & 7) + ((lane >> 3) & 1) * 8) * 32 + (lane >> 4) * 16;
      const uint32_t kv0 = sd + (OFF_KV >> 4);
      float sA[32], sB[32], o[12], oB[12];
      uint32_t pL[16], pH[16], q[4], qB[4];
      float mc0, mc1;
      const uint32_t zacc = (uint32_t)P.pad[0];
      const bool first_rows = lhi == l3;
      const int xbase = u - 16 * warp;
      uint32_t pend = 0;
#define KDH(kv, l, hf) desc32(((kv) + (l) * 256 + (hf) * 64) | 0x10000u)
#define VD(kv, l) (onesw - ((kv) + (l) * 256 + 128) * 65535u)
#define VDH(kv, l, hf) (onesw - ((kv) + (l) * 256 + 128 + (hf) * 64) * 65535u)
#define STAGE_O(hh, o)                                                                                   \
      do {                                                                                               \
        const float i0 = rcpf(o[8]), i1 = rcpf(o[10]);                                                   \
        stsm4(ost + (hh) * 4096, pack2(o[0] * i0, o[1] * i0), pack2(o[2] * i1, o[3] * i1),               \
              pack2(o[4] * i0, o[5] * i0), pack2(o[6] * i1, o[7] * i1));                                 \
        fence_async_smem();                                                                              \
        __syncwarp();                                                                                    \
        if (lane == 0) mbar_arrive(bar + B_OST + 8 * (hh));                                              \
      } while (0)
#define ROWSUMS(o)
#define EXPS0(s, m0, m1, o) exps(s, m0, m1)
#define EXPS1(s, m0, m1, o) exps(s, m0, m1)
#define XO(o)
#define FINALIZE(hh, o)                                                                                  \
      do {                                                                                               \
        ROWSUMS(o)                                                                                       \
        const float z0 = fmaf(o[0], 0.f, fmaf(o[1], 0.f, fmaf(o[4], 0.f, fmaf(o[5], 0.f, o[8]))));       \
        const float z1 = fmaf(o[2], 0.f, fmaf(o[3], 0.f, fmaf(o[6], 0.f, fmaf(o[7], 0.f, o[10]))));      \
        if (__all_sync(~0u, z0 <= ATT_LMAX && z1 <= ATT_LMAX)) STAGE_O(hh, o);                           \
        else pend |= 1u << (hh);                                                                         \
      } while (0)
#define LOAD_Q(qq, hh) asm volatile("ld.shared.v4.u32 {%0, %1, %2, %3}, [%4];" : "=r"(qq[0]), "=r"(qq[1]), "=r"(qq[2]), "=r"(qq[3]) : "r"(qs + (hh) * 4096))
#define S_FULL(s, qq, kv, l)                                                                             \
      do {                                                                                               \
        wgmma_rs_n32<0, 0>(s, qq[0], qq[1], qq[2], qq[3], KDH(kv, l, 0), zacc);                          \
        wgmma_rs_n32<0, 16>(s, qq[0], qq[1], qq[2], qq[3], KDH(kv, l, 1), zacc);                         \
      } while (0)
#define S_MIX(s, qq, kv, hf)                                                                             \
      do {                                                                                               \
        wgmma_rs_n32<0, 0>(s, qq[0], qq[1], qq[2], qq[3], KDH(kv, llo, hf), zacc);                       \
        wgmma_rs_n32<0, 16>(s, qq[0], qq[1], qq[2], qq[3], KDH(kv, lhi, hf), zacc);                      \
      } while (0)
#define HEAD(h, s0, s1, p0, p1, oc, op, qc, qn)                                                          \
      do {                                                                                               \
        const uint32_t kv = kv0 + ((h) & 1) * 1536, kvn = kv0 + (((h) + 1) & 1) * 1536;                  \
                                                  \
        if (first_rows) {                                                                                \
          _Pragma("unroll") for (int i = 0; i < 32; i++) {                                               \
            const int x = xbase + (i >> 3) * 16 + ((i >> 2) & 1) * 8 - ((i >> 1) & 1) * 8 + (i & 1);     \
            s0[i] = x <= 0 ? s0[i] : -INFINITY;                                                          \
          }                                                                                              \
        }                                                                                                \
        rowmax(s0, mc0, mc1);                                                                            \
        mc0 = fmaf(mc0, -SC, -ATT_OFF); mc1 = fmaf(mc1, -SC, -ATT_OFF);                                  \
        EXPS0(s0, mc0 + vb3, mc1 + vb3, oc);                                                                  \
        packp(s0, p0);                                                                                   \
        fregs(p0); fregs(s0); fregs(oc);                                                                 \
        wgmma_fence();                                                                                   \
        issue_pv<1>(oc, p0, VD(kv, l3));                                                                 \
        S_FULL(s0, qc, kv, l1);                                                                          \
        wgmma_commit();                                                                                  \
        wgmma_wait<1>();                                                                                 \
        fregs(s1); fregs(op); fregs(p1);                                                                 \
        if ((h) > 0 && (h) < 3 && lane == 0) mbar_arrive(bar + B_KVEMPTY + 8 * (((h) - 1) & 1));         \
        if ((h) > 0) { FINALIZE((h) - 1, op); }                                                          \
                                                                                         \
        EXPS1(s1, mc0 + vb2, mc1 + vb2, oc);                                                                  \
        packp(s1, p1);                                                                                   \
        fregs(p1); fregs(s1);                                                                            \
        wgmma_fence();                                                                                   \
        issue_pv<0>(oc, p1, VD(kv, l2));                                                                 \
        S_MIX(s1, qc, kv, 0);                                                                            \
        wgmma_commit();                                                                                  \
        wgmma_wait<1>();                                                                                 \
        fregs(s0); fregs(p0);                                                                            \
                                                                                         \
        EXPS1(s0, mc0 + vb1, mc1 + vb1, oc);                                                                  \
        packp(s0, p0);                                                                                   \
        fregs(p0); fregs(s0);                                                                            \
        wgmma_fence();                                                                                   \
        issue_pv<0>(oc, p0, VD(kv, l1));                                                                 \
        S_MIX(s0, qc, kv, 1);                                                                            \
        wgmma_commit();                                                                                  \
        wgmma_wait<1>();                                                                                 \
        fregs(s1); fregs(p1);                                                                            \
                                                   \
        LOAD_Q(qn, ((h) + 1) & 3);                                                                       \
        WARP_SWITCH(x_exp, s1, p1, mc0, mc1, vbl, c0, c1, Mx XO(oc));                                           \
        fregs(p1); fregs(s1); fregs(qn);                                                                 \
        if ((h) < 3) mbar_wait(bar + B_KVFULL + 8 * (((h) + 1) & 1), (((h) + 1) >> 1) & 1);              \
        wgmma_fence();                                                                                   \
        issue_pv2(oc, p1, VDH(kv, llo, 0), VDH(kv, lhi, 0));                                             \
        S_FULL(s1, qn, kvn, l3);                                                                         \
        wgmma_commit();                                                                                  \
        wgmma_wait<1>();                                                                                 \
        fregs(s0); fregs(p0);                                                                            \
                                                                                   \
        WARP_SWITCH(y_exp, s0, p0, mc0, mc1, vbl, c0, c1, Mx XO(oc));                                           \
        fregs(p0); fregs(s0);                                                                            \
        wgmma_fence();                                                                                   \
        issue_pv2(oc, p0, VDH(kv, llo, 1), VDH(kv, lhi, 1));                                             \
        S_FULL(s0, qn, kvn, l2);                                                                         \
        wgmma_commit();                                                                                  \
        wgmma_wait<1>();                                                                                 \
        fregs(s1); fregs(p1);                                                                            \
      } while (0)

#pragma unroll
      for (int i = 0; i < 12; i++) o[i] = oB[i] = 0.f;
      LOAD_Q(q, 0);
      mbar_wait(bar + B_KVFULL, 0);
      fregs(q); fregs(sA); fregs(sB); fregs(o); fregs(oB);
      wgmma_fence();
      S_FULL(sA, q, kv0, l3);
      wgmma_commit();
      S_FULL(sB, q, kv0, l2);
      wgmma_commit();
      wgmma_wait<1>();
      fregs(sA);
#pragma unroll 1
      for (int h = 0; h < 4; h += 2) {
        HEAD(h, sA, sB, pL, pH, o, oB, q, qB);
        HEAD(h + 1, sB, sA, pH, pL, oB, o, qB, q);
      }
      wgmma_wait<0>();
      fregs(oB); fregs(sA); fregs(sB);
      FINALIZE(3, oB);
      if (bar_red_or(pend != 0)) {
        uint32_t use = 0;
#pragma unroll 1
        for (int h = 0; h < 4; h++) {
          if (!bar_red_or((pend >> h) & 1)) continue;
          if (threadIdx.x == 256) {
            const uint32_t bytes = (6 - lb0) * 4096;
            mbar_expect_tx(bar + B_KVFULL, bytes);
            bulk_load(sb + OFF_KV + lb0 * 4096, P.kv + (size_t)((nb1 * 4 + h) * 32 + 2 * rb - 4 + lb0) * 4096, bytes, bar + B_KVFULL);
          }
          asm volatile("ld.shared.v4.u32 {%0, %1, %2, %3}, [%4];" : "=r"(q[0]), "=r"(q[1]), "=r"(q[2]), "=r"(q[3]) : "r"(qs + h * 4096));
          mbar_wait(bar + B_KVFULL, use & 1);
          use++;
          float m0 = -INFINITY, m1 = -INFINITY;
#pragma unroll
          for (int i = 0; i < 12; i++) o[i] = 0.f;
#pragma unroll 1
          for (int tt = 0; tt < 5; tt++) {
            const int l = lhi - tt;
            if (l < lb0) break;
            fregs(q); fregs(sA);
            wgmma_fence();
            S_FULL(sA, q, kv0, l);
            wgmma_commit();
            wgmma_wait<0>();
            fregs(sA);
            const int ta = tt == 4 ? 0 : -1000, tb = tt == 0 ? 0 : 1000;
#pragma unroll
            for (int i = 0; i < 32; i++) {
              const int x = xbase + (i >> 3) * 16 + ((i >> 2) & 1) * 8 - ((i >> 1) & 1) * 8 + (i & 1);
              sA[i] = (x > ta && x <= tb) ? sA[i] : -INFINITY;
            }
            float x0, x1;
            rowmax(sA, x0, x1);
            const float n0 = fmaxf(m0, x0), n1 = fmaxf(m1, x1);
            const float al0 = ex2((m0 - n0) * SC), al1 = ex2((m1 - n1) * SC);
            m0 = n0; m1 = n1;
            exps(sA, -n0 * SC, -n1 * SC);
#pragma unroll
            for (int i = 0; i < 12; i++) o[i] *= (i & 2) ? al1 : al0;
            packp(sA, pL);
            fregs(pL); fregs(o);
            wgmma_fence();
            issue_pv_sum(o, pL, VD(kv0, l));
            wgmma_commit();
            wgmma_wait<0>();
            fregs(o); fregs(pL);
          }
          if ((pend >> h) & 1) STAGE_O(h, o);
        }
      }
    }
    __syncwarp();
    cluster_arrive();
    cluster_wait();
  }
}

namespace {
typedef CUresult (*EncodeFn)(CUtensorMap*, CUtensorMapDataType, cuuint32_t, void*, const cuuint64_t*, const cuuint64_t*,
                             const cuuint32_t*, const cuuint32_t*, CUtensorMapInterleave, CUtensorMapSwizzle,
                             CUtensorMapL2promotion, CUtensorMapFloatOOBfill);

void make_map(EncodeFn fn, CUtensorMap* m, const void* ptr, uint64_t cols, uint64_t rows, uint32_t box_cols, uint32_t box_rows,
              CUtensorMapSwizzle sw = CU_TENSOR_MAP_SWIZZLE_128B) {
  cuuint64_t dims[2] = {cols, rows};
  cuuint64_t strides[1] = {cols * 2};
  cuuint32_t box[2] = {box_cols, box_rows};
  cuuint32_t es[2] = {1, 1};
  fn(m, CU_TENSOR_MAP_DATA_TYPE_BFLOAT16, 2, const_cast<void*>(ptr), dims, strides, box, es, CU_TENSOR_MAP_INTERLEAVE_NONE,
     sw, CU_TENSOR_MAP_L2_PROMOTION_L2_128B, CU_TENSOR_MAP_FLOAT_OOB_FILL_NONE);
}
}

extern "C" void kernel_launch(void* const* d_in, const int* in_sizes, int n_in, void* d_out, int out_size) {
  (void)in_sizes; (void)n_in; (void)out_size;
  static EncodeFn enc = nullptr;
  static void *p_ab = nullptr, *p_o = nullptr, *p_kv = nullptr, *p_flags = nullptr, *p_epoch = nullptr;
  if (!enc) {
    void* p = nullptr;
    cudaDriverEntryPointQueryResult st;
    cudaGetDriverEntryPoint("cuTensorMapEncodeTiled", &p, cudaEnableDefault, &st);
    enc = (EncodeFn)p;
    cudaGetSymbolAddress(&p_ab, g_ab);
    cudaGetSymbolAddress(&p_o, g_o);
    cudaGetSymbolAddress(&p_kv, g_kv);
    cudaGetSymbolAddress(&p_flags, g_flags);
    cudaGetSymbolAddress(&p_epoch, g_epoch);
    cudaFuncSetAttribute(concat_heads__spectral_fnet__sliding_block__prompt_kernel,
                         cudaFuncAttributeMaxDynamicSharedMemorySize, SMEM_BYTES);
  }
  Params P;
  make_map(enc, &P.xa, d_in[0], 512, 2048, 64, 64);
  make_map(enc, &P.cr, d_in[1], 2048, 2048, 64, 64);
  make_map(enc, &P.ci, d_in[2], 2048, 2048, 64, 64);
  make_map(enc, &P.wr, d_in[3], 512, 512, 64, 128);
  make_map(enc, &P.wi, d_in[4], 512, 512, 64, 128);
  make_map(enc, &P.xb, d_in[5], 512, 2048, 64, 64);
  make_map(enc, &P.wqkv, d_in[6], 1536, 512, 64, 64);
  {
    cuuint64_t dims[4] = {512, 16, 4, 8};
    cuuint64_t strides[3] = {1024, 16 * 1024, 64 * 1024};
    cuuint32_t box[4] = {64, 16, 1, 4};
    cuuint32_t es[4] = {1, 1, 1, 1};
    enc(&P.wo4, CU_TENSOR_MAP_DATA_TYPE_BFLOAT16, 4, d_in[7], dims, strides, box, es, CU_TENSOR_MAP_INTERLEAVE_NONE,
        CU_TENSOR_MAP_SWIZZLE_128B, CU_TENSOR_MAP_L2_PROMOTION_L2_128B, CU_TENSOR_MAP_FLOAT_OOB_FILL_NONE);
  }
  make_map(enc, &P.o, p_o, 512, 2048, 64, 64);
  make_map(enc, &P.o16, p_o, 512, 2048, 16, 128, CU_TENSOR_MAP_SWIZZLE_NONE);
  make_map(enc, &P.out, d_out, 1024, 2048, 64, 64);
  P.flags = (unsigned*)p_flags; P.epoch = (unsigned*)p_epoch; P.kv = (uint8_t*)p_kv;
  P.ab = (uint8_t*)p_ab; P.p_xb = (const uint8_t*)d_in[5]; P.p_wq = (const uint8_t*)d_in[6];
  P.p_wo = (const uint8_t*)d_in[7]; P.pad[0] = 0;
  P.p_xa = (const uint8_t*)d_in[0]; P.p_cr = (const uint8_t*)d_in[1]; P.p_ci = (const uint8_t*)d_in[2];
  P.p_wr = (const uint8_t*)d_in[3]; P.p_wi = (const uint8_t*)d_in[4];
  concat_heads__spectral_fnet__sliding_block__prompt_kernel<<<128, 512, SMEM_BYTES>>>(P);
}
```
